```python
import torch

def _softmax(x, axis=-1):
    return torch.softmax(x, dim=axis)

def _gelu(x):
    return torch.nn.functional.gelu(x, approximate='tanh')

def _silu(x):
    return torch.nn.functional.silu(x)

def _sigmoid(x):
    return torch.sigmoid(x)

def _layernorm(x, axis=-1, eps=1e-05):
    m = x.mean(dim=axis, keepdim=True)
    v = x.var(dim=axis, keepdim=True, unbiased=False)
    return (x - m) / torch.sqrt(v + eps)

def _scatter_add(tgt, idx, src, axis=0):
    return tgt.clone().index_add_(axis, idx, src)

def _segment_sum(src, seg, n):
    out = torch.zeros((n,) + src.shape[1:], dtype=src.dtype)
    return out.index_add_(0, seg, src)

def _pad(x, pw):
    flat = tuple((v for pair in reversed(pw) for v in pair))
    return torch.nn.functional.pad(x, flat)
kernel_name = 'recurrent_scan__ssm_conv_h3__mixer_gmlp__prompt'

def setup_inputs():

    _w = lambda a: (lambda t: t.to(torch.bfloat16) if t.is_floating_point() else t)(torch.as_tensor(a))

    def _A_setup():
        B, S, D = (1, 2048, 448)
        ks = 4
        return {'q': _w((lambda *s: torch.randn(*s, dtype=torch.bfloat16) * 0.05)(B, S, D)), 'k': _w((lambda *s: torch.randn(*s, dtype=torch.bfloat16) * 0.2)(B, S, D)), 'v': _w((lambda *s: torch.randn(*s, dtype=torch.bfloat16) * 0.2)(B, S, D)), 'shift_k': _w((lambda *s: torch.randn(*s, dtype=torch.bfloat16) * 0.2)(D, ks) * 0.5), 'ssm_k': _w((lambda *s: torch.randn(*s, dtype=torch.bfloat16) * 0.2)(D, S) * (1.0 / S ** 0.5)), 'ssm_D': _w((lambda *s: torch.randn(*s, dtype=torch.bfloat16) * 0.2)(D))}
    _A_in = _A_setup()

    def _B_setup():
        B, S, D, F = (1, 2048, 448, 1792)
        Fh = F // 2
        return {'x': _w((lambda *s: torch.randn(*s, dtype=torch.bfloat16) * 0.05)(B, S, D)), 'w_in': _w((lambda *s: torch.randn(*s, dtype=torch.bfloat16) * 0.8)(D, 2 * Fh)), 'w_sp': _w(0.01 * (lambda *s: torch.randn(*s, dtype=torch.bfloat16) * 0.8)(S, S)), 'b_sp': _w(1.0 + 0.01 * (lambda *s: torch.randn(*s, dtype=torch.bfloat16) * 0.1)(S)), 'w_out': _w((lambda *s: torch.randn(*s, dtype=torch.bfloat16) * 0.1)(Fh, D))}
    _B_in = _B_setup()
    return {'A_q': _A_in['q'], 'A_k': _A_in['k'], 'A_v': _A_in['v'], 'A_shift_k': _A_in['shift_k'], 'A_ssm_k': _A_in['ssm_k'], 'A_ssm_D': _A_in['ssm_D'], 'B_x': _B_in['x'], 'B_w_in': _B_in['w_in'], 'B_w_sp': _B_in['w_sp'], 'B_b_sp': _B_in['b_sp'], 'B_w_out': _B_in['w_out']}

def reference(A_q, A_k, A_v, A_shift_k, A_ssm_k, A_ssm_D, B_x, B_w_in, B_w_sp, B_b_sp, B_w_out):

    def _A_ref(q, k, v, shift_k, ssm_k, ssm_D):
        B, S, D = q.shape
        ks = shift_k.shape[-1]
        k_pad = _pad(k, ((0, 0), (ks - 1, 0), (0, 0)))
        k_shift = torch.zeros_like(k)
        for t in range(ks):
            k_shift = k_shift + k_pad[:, t:t + S, :] * shift_k[:, ks - 1 - t][None, None, :]
        kv = k_shift * v
        L = 2 * S
        kv_pad = _pad(kv, ((0, 0), (0, S), (0, 0)))
        kf_pad = _pad(ssm_k, ((0, 0), (0, S)))
        kv_f = (lambda x, axes=(-2, -1): torch.fft.rfft2(x.float(), dim=axes))(kv_pad[:, None, :, :], axes=(1, 2))
        kf_f = (lambda x, axes=(-2, -1): torch.fft.rfft2(x.float(), dim=axes))(kf_pad[:, None, :], axes=(1, 2))
        kf_f = (lambda x, *d: x.permute(*d))(kf_f, 1, 2, 0)
        y_f = kv_f * kf_f[None, :, :, :]
        y = (lambda x, s, axes=(-2, -1): torch.fft.irfft2(x, s=s, dim=axes).to(torch.bfloat16))(y_f, (1, L), axes=(1, 2))[:, 0, :S, :]
        y = y + kv * ssm_D[None, None, :]
        return q * y

    def _B_ref(x, w_in, w_sp, b_sp, w_out):
        B, S, D = x.shape
        F = w_in.shape[-1]
        Fh = F // 2
        z = _gelu(torch.einsum('bsd,df->bsf', x, w_in))
        z1 = z[..., :Fh].clone()
        z2 = _layernorm(z[..., Fh:], axis=-1)
        g = torch.einsum('ts,bsf->btf', w_sp, z2) + b_sp[None, :, None]
        return torch.einsum('bsf,fd->bsd', z1 * g, w_out)
    x = A_q
    xn = _layernorm(x, axis=-1)
    s = _A_ref(xn, A_k, A_v, A_shift_k, A_ssm_k, A_ssm_D)
    g = _silu(_B_ref(xn, B_w_in, B_w_sp, B_b_sp, B_w_out))
    return x + s * g
```

```cpp
#include <cuda_runtime.h>
#include <cuda.h>
#include <cuda_bf16.h>
#include <stdint.h>

#define DEVI __device__ __forceinline__
DEVI uint32_t smem_u32(const void* p) { return (uint32_t)__cvta_generic_to_shared(p); }
DEVI void wg_fence() { asm volatile("wgmma.fence.sync.aligned;\n" ::: "memory"); }
DEVI void wg_commit() { asm volatile("wgmma.commit_group.sync.aligned;\n" ::: "memory"); }
template<int N> DEVI void wg_wait() { asm volatile("wgmma.wait_group.sync.aligned %0;\n" :: "n"(N) : "memory"); }
DEVI uint64_t make_desc(uint32_t addr, uint32_t lbo, uint32_t sbo, uint32_t swz) {
  return (uint64_t)((addr & 0x3FFFF) >> 4) | ((uint64_t)(lbo >> 4) << 16) | ((uint64_t)(sbo >> 4) << 32) | ((uint64_t)swz << 62);
}
DEVI void mbar_init(uint32_t bar, uint32_t cnt) { asm volatile("mbarrier.init.shared::cta.b64 [%0], %1;" :: "r"(bar), "r"(cnt) : "memory"); }
DEVI void mbar_expect_tx(uint32_t bar, uint32_t bytes) { asm volatile("mbarrier.arrive.expect_tx.shared::cta.b64 _, [%0], %1;" :: "r"(bar), "r"(bytes) : "memory"); }
DEVI void mbar_arrive(uint32_t bar) { asm volatile("mbarrier.arrive.shared::cta.b64 _, [%0];" :: "r"(bar) : "memory"); }
DEVI void mbar_arrive_remote(uint32_t bar, uint32_t cta) {
  asm volatile("{\n.reg .b32 ra;\nmapa.shared::cluster.u32 ra, %0, %1;\nmbarrier.arrive.shared::cluster.b64 _, [ra];\n}\n" :: "r"(bar), "r"(cta) : "memory");
}
DEVI bool mbar_try(uint32_t bar, uint32_t parity) {
  uint32_t done;
  asm volatile("{\n.reg .pred p;\nmbarrier.try_wait.parity.shared::cta.b64 p, [%1], %2;\nselp.u32 %0, 1, 0, p;\n}\n" : "=r"(done) : "r"(bar), "r"(parity) : "memory");
  return done;
}
DEVI bool mbar_test(uint32_t bar, uint32_t parity) {
  uint32_t done;
  asm volatile("{\n.reg .pred p;\nmbarrier.test_wait.parity.shared::cta.b64 p, [%1], %2;\nselp.u32 %0, 1, 0, p;\n}\n" : "=r"(done) : "r"(bar), "r"(parity) : "memory");
  return done;
}
DEVI void mbar_wait(uint32_t bar, uint32_t parity) {
  asm volatile("{\n.reg .pred p, q;\n.reg .u32 c;\nmov.u32 c, 0;\n"
               "W%=:\nmbarrier.try_wait.parity.shared::cta.b64 p, [%0], %1;\n@p bra D%=;\n"
               "add.u32 c, c, 1;\nsetp.lt.u32 q, c, 4194304;\n@q bra W%=;\nD%=:\n}\n" :: "r"(bar), "r"(parity) : "memory");
}
DEVI void fence_async_smem() { asm volatile("fence.proxy.async.shared::cta;\n" ::: "memory"); }
DEVI void fence_async_all() { asm volatile("fence.proxy.async;\n" ::: "memory"); }
DEVI void bar_sync(int id, int n) { asm volatile("bar.sync %0, %1;" :: "r"(id), "r"(n) : "memory"); }
DEVI void bar_arrive(int id, int n) { asm volatile("bar.arrive %0, %1;" :: "r"(id), "r"(n) : "memory"); }
DEVI void bulk_g2s(uint32_t dst, const void* src, uint32_t bytes, uint32_t bar) {
  asm volatile("cp.async.bulk.shared::cluster.global.mbarrier::complete_tx::bytes [%0], [%1], %2, [%3];" :: "r"(dst), "l"(src), "r"(bytes), "r"(bar) : "memory");
}
DEVI void bulk_s2g(void* dst, uint32_t src, uint32_t bytes) {
  asm volatile("cp.async.bulk.global.shared::cta.bulk_group [%0], [%1], %2;" :: "l"(dst), "r"(src), "r"(bytes) : "memory");
}
DEVI void bulk_commit() { asm volatile("cp.async.bulk.commit_group;" ::: "memory"); }
template<int N> DEVI void bulk_wait() { asm volatile("cp.async.bulk.wait_group %0;" :: "n"(N) : "memory"); }
template<int N> DEVI void bulk_wait_read() { asm volatile("cp.async.bulk.wait_group.read %0;" :: "n"(N) : "memory"); }
DEVI void tma2d(uint32_t dst, const CUtensorMap* tm, int c0, int c1, uint32_t bar) {
  asm volatile("cp.async.bulk.tensor.2d.shared::cluster.global.mbarrier::complete_tx::bytes [%0], [%1, {%3, %4}], [%2];" :: "r"(dst), "l"(tm), "r"(bar), "r"(c0), "r"(c1) : "memory");
}
DEVI void tma2d_mc(uint32_t dst, const CUtensorMap* tm, int c0, int c1, uint32_t bar, uint16_t mask) {
  asm volatile("cp.async.bulk.tensor.2d.shared::cluster.global.mbarrier::complete_tx::bytes.multicast::cluster [%0], [%1, {%3, %4}], [%2], %5;" :: "r"(dst), "l"(tm), "r"(bar), "r"(c0), "r"(c1), "h"(mask) : "memory");
}
DEVI void tma3d(uint32_t dst, const CUtensorMap* tm, int c0, int c1, int c2, uint32_t bar) {
  asm volatile("cp.async.bulk.tensor.3d.shared::cluster.global.mbarrier::complete_tx::bytes [%0], [%1, {%3, %4, %5}], [%2];" :: "r"(dst), "l"(tm), "r"(bar), "r"(c0), "r"(c1), "r"(c2) : "memory");
}
DEVI void tma2d_store(const CUtensorMap* tm, uint32_t src, int c0, int c1) {
  asm volatile("cp.async.bulk.tensor.2d.global.shared::cta.bulk_group [%0, {%2, %3}], [%1];" :: "l"(tm), "r"(src), "r"(c0), "r"(c1) : "memory");
}
DEVI void tma2d_prefetch(const CUtensorMap* tm, int c0, int c1) {
  asm volatile("cp.async.bulk.prefetch.tensor.2d.L2.global [%0, {%1, %2}];" :: "l"(tm), "r"(c0), "r"(c1) : "memory");
}
DEVI void prefetch_tmap(const CUtensorMap* tm) { asm volatile("prefetch.tensormap [%0];" :: "l"(tm) : "memory"); }
DEVI uint32_t lds32(uint32_t a) { uint32_t v; asm volatile("ld.shared.u32 %0, [%1];" : "=r"(v) : "r"(a) : "memory"); return v; }
DEVI uint2 lds64(uint32_t a) { uint2 v; asm volatile("ld.shared.v2.u32 {%0,%1}, [%2];" : "=r"(v.x), "=r"(v.y) : "r"(a) : "memory"); return v; }
DEVI uint4 lds128(uint32_t a) { uint4 v; asm volatile("ld.shared.v4.u32 {%0,%1,%2,%3}, [%4];" : "=r"(v.x), "=r"(v.y), "=r"(v.z), "=r"(v.w) : "r"(a) : "memory"); return v; }
DEVI void sts16(uint32_t a, uint16_t v) { asm volatile("st.shared.u16 [%0], %1;" :: "r"(a), "h"(v) : "memory"); }
DEVI void sts32(uint32_t a, uint32_t v) { asm volatile("st.shared.u32 [%0], %1;" :: "r"(a), "r"(v) : "memory"); }
DEVI void sts64(uint32_t a, uint32_t x, uint32_t y) { asm volatile("st.shared.v2.u32 [%0], {%1,%2};" :: "r"(a), "r"(x), "r"(y) : "memory"); }
DEVI void sts128(uint32_t a, uint32_t x, uint32_t y, uint32_t z, uint32_t w) { asm volatile("st.shared.v4.u32 [%0], {%1,%2,%3,%4};" :: "r"(a), "r"(x), "r"(y), "r"(z), "r"(w) : "memory"); }
DEVI void stsm4(uint32_t a, uint32_t x, uint32_t y, uint32_t z, uint32_t w) { asm volatile("stmatrix.sync.aligned.m8n8.x4.shared.b16 [%0], {%1,%2,%3,%4};" :: "r"(a), "r"(x), "r"(y), "r"(z), "r"(w) : "memory"); }
DEVI void stsm4t(uint32_t a, uint32_t x, uint32_t y, uint32_t z, uint32_t w) { asm volatile("stmatrix.sync.aligned.m8n8.x4.trans.shared.b16 [%0], {%1,%2,%3,%4};" :: "r"(a), "r"(x), "r"(y), "r"(z), "r"(w) : "memory"); }
DEVI void ldsm4(uint32_t a, uint32_t& x, uint32_t& y, uint32_t& z, uint32_t& w) { asm volatile("ldmatrix.sync.aligned.m8n8.x4.shared.b16 {%0,%1,%2,%3}, [%4];" : "=r"(x), "=r"(y), "=r"(z), "=r"(w) : "r"(a) : "memory"); }
DEVI void ldsm4t(uint32_t a, uint32_t& x, uint32_t& y, uint32_t& z, uint32_t& w) { asm volatile("ldmatrix.sync.aligned.m8n8.x4.trans.shared.b16 {%0,%1,%2,%3}, [%4];" : "=r"(x), "=r"(y), "=r"(z), "=r"(w) : "r"(a) : "memory"); }
DEVI uint32_t pack_bf16(float lo, float hi) { uint32_t r; asm("cvt.rn.bf16x2.f32 %0, %1, %2;" : "=r"(r) : "f"(hi), "f"(lo)); return r; }
DEVI float bf_lo(uint32_t w) { return __uint_as_float(w << 16); }
DEVI float bf_hi(uint32_t w) { return __uint_as_float(w & 0xffff0000u); }
DEVI uint32_t hfma2(uint32_t a, uint32_t b, uint32_t c) { uint32_t r; asm("fma.rn.bf16x2 %0, %1, %2, %3;" : "=r"(r) : "r"(a), "r"(b), "r"(c)); return r; }
DEVI uint32_t hmul2(uint32_t a, uint32_t b) { uint32_t r; asm("mul.rn.bf16x2 %0, %1, %2;" : "=r"(r) : "r"(a), "r"(b)); return r; }
DEVI uint32_t hadd2(uint32_t a, uint32_t b) { uint32_t r; asm("add.rn.bf16x2 %0, %1, %2;" : "=r"(r) : "r"(a), "r"(b)); return r; }
DEVI uint32_t prmt(uint32_t a, uint32_t b, uint32_t s) { uint32_t r; asm("prmt.b32 %0, %1, %2, %3;" : "=r"(r) : "r"(a), "r"(b), "r"(s)); return r; }
DEVI float tanh_fast(float x) { float r; asm("tanh.approx.f32 %0, %1;" : "=f"(r) : "f"(x)); return r; }
DEVI void st_release(uint32_t* p, uint32_t v) { asm volatile("st.release.gpu.global.u32 [%0], %1;" :: "l"(p), "r"(v) : "memory"); }
DEVI void st_relaxed(uint32_t* p, uint32_t v) { asm volatile("st.relaxed.gpu.global.u32 [%0], %1;" :: "l"(p), "r"(v) : "memory"); }
DEVI uint32_t ld_acquire(const uint32_t* p) { uint32_t v; asm volatile("ld.acquire.gpu.global.u32 %0, [%1];" : "=r"(v) : "l"(p) : "memory"); return v; }
DEVI uint32_t ld_relaxed(const uint32_t* p) { uint32_t v; asm volatile("ld.relaxed.gpu.global.u32 %0, [%1];" : "=r"(v) : "l"(p) : "memory"); return v; }
template<int R> DEVI void reg_inc() { asm volatile("setmaxnreg.inc.sync.aligned.u32 %0;" :: "n"(R)); }
template<int R> DEVI void reg_dec() { asm volatile("setmaxnreg.dec.sync.aligned.u32 %0;" :: "n"(R)); }
DEVI uint32_t cluster_rank() { uint32_t r; asm volatile("mov.u32 %0, %%cluster_ctarank;" : "=r"(r)); return r; }
DEVI void cluster_arrive() { asm volatile("barrier.cluster.arrive.release.aligned;\n" ::: "memory"); }
DEVI void cluster_arrive_relaxed() { asm volatile("barrier.cluster.arrive.relaxed.aligned;\n" ::: "memory"); }
DEVI void cluster_wait() { asm volatile("barrier.cluster.wait.aligned;\n" ::: "memory"); }

#define ELECT_PRE "{\n.reg .pred e;\nelect.sync _|e, 0xffffffff;\n@e "
DEVI void e_tma2d(uint32_t dst, const CUtensorMap* tm, int c0, int c1, uint32_t bar) {
  asm volatile(ELECT_PRE "cp.async.bulk.tensor.2d.shared::cluster.global.mbarrier::complete_tx::bytes [%0], [%1, {%3, %4}], [%2];\n}" :: "r"(dst), "l"(tm), "r"(bar), "r"(c0), "r"(c1) : "memory");
}
DEVI void e_tma3d(uint32_t dst, const CUtensorMap* tm, int c0, int c1, int c2, uint32_t bar) {
  asm volatile(ELECT_PRE "cp.async.bulk.tensor.3d.shared::cluster.global.mbarrier::complete_tx::bytes [%0], [%1, {%3, %4, %5}], [%2];\n}" :: "r"(dst), "l"(tm), "r"(bar), "r"(c0), "r"(c1), "r"(c2) : "memory");
}
DEVI void e_tma2d_mc(uint32_t dst, const CUtensorMap* tm, int c0, int c1, uint32_t bar, uint16_t mask) {
  asm volatile(ELECT_PRE "cp.async.bulk.tensor.2d.shared::cluster.global.mbarrier::complete_tx::bytes.multicast::cluster [%0], [%1, {%3, %4}], [%2], %5;\n}"
    :: "r"(dst), "l"(tm), "r"(bar), "r"(c0), "r"(c1), "h"(mask) : "memory");
}
DEVI void e_tma3d_mc(uint32_t dst, const CUtensorMap* tm, int c0, int c1, int c2, uint32_t bar, uint16_t mask) {
  asm volatile(ELECT_PRE "cp.async.bulk.tensor.3d.shared::cluster.global.mbarrier::complete_tx::bytes.multicast::cluster [%0], [%1, {%3, %4, %5}], [%2], %6;\n}"
    :: "r"(dst), "l"(tm), "r"(bar), "r"(c0), "r"(c1), "r"(c2), "h"(mask) : "memory");
}
DEVI void e_pf2d(const CUtensorMap* tm, int c0, int c1) {
  asm volatile(ELECT_PRE "cp.async.bulk.prefetch.tensor.2d.L2.global [%0, {%1, %2}];\n}" :: "l"(tm), "r"(c0), "r"(c1) : "memory");
}
DEVI void e_pf3d(const CUtensorMap* tm, int c0, int c1, int c2) {
  asm volatile(ELECT_PRE "cp.async.bulk.prefetch.tensor.3d.L2.global [%0, {%1, %2, %3}];\n}" :: "l"(tm), "r"(c0), "r"(c1), "r"(c2) : "memory");
}
DEVI void e_pftm(const CUtensorMap* tm) { asm volatile(ELECT_PRE "prefetch.tensormap [%0];\n}" :: "l"(tm) : "memory"); }
DEVI void e_init(uint32_t bar, uint32_t cnt) { asm volatile(ELECT_PRE "mbarrier.init.shared::cta.b64 [%0], %1;\n}" :: "r"(bar), "r"(cnt) : "memory"); }
DEVI void e_arrive(uint32_t bar) { asm volatile(ELECT_PRE "mbarrier.arrive.shared::cta.b64 _, [%0];\n}" :: "r"(bar) : "memory"); }
DEVI void e_arrive_remote(uint32_t bar, uint32_t cta) {
  asm volatile("{\n.reg .pred e;\n.reg .b32 ra;\nmapa.shared::cluster.u32 ra, %0, %1;\nelect.sync _|e, 0xffffffff;\n@e mbarrier.arrive.shared::cluster.b64 _, [ra];\n}" :: "r"(bar), "r"(cta) : "memory");
}
DEVI void e_store3d_flag(const CUtensorMap* tm, uint32_t src, int c0, int c1, int c2, uint32_t* flag, uint32_t v) {
  asm volatile("{\n.reg .pred e;\nelect.sync _|e, 0xffffffff;\n"
    "@e cp.async.bulk.tensor.3d.global.shared::cta.bulk_group [%0, {%2, %3, %4}], [%1];\n@e cp.async.bulk.commit_group;\n@e cp.async.bulk.wait_group 0;\n"
    "@e st.relaxed.gpu.global.u32 [%5], %6;\n}" :: "l"(tm), "r"(src), "r"(c0), "r"(c1), "r"(c2), "l"(flag), "r"(v) : "memory");
}
DEVI void e_store2d(const CUtensorMap* tm, uint32_t src, int c0, int c1) {
  asm volatile("{\n.reg .pred e;\nelect.sync _|e, 0xffffffff;\n"
    "@e cp.async.bulk.tensor.2d.global.shared::cta.bulk_group [%0, {%2, %3}], [%1];\n@e cp.async.bulk.commit_group;\n@e cp.async.bulk.wait_group.read 0;\n}"
    :: "l"(tm), "r"(src), "r"(c0), "r"(c1) : "memory");
}
DEVI void e_store3d(const CUtensorMap* tm, uint32_t src, int c0, int c1, int c2) {
  asm volatile("{\n.reg .pred e;\nelect.sync _|e, 0xffffffff;\n"
    "@e cp.async.bulk.tensor.3d.global.shared::cta.bulk_group [%0, {%2, %3, %4}], [%1];\n@e cp.async.bulk.commit_group;\n}"
    :: "l"(tm), "r"(src), "r"(c0), "r"(c1), "r"(c2) : "memory");
}
DEVI void e_wait_flag(uint32_t* flag, uint32_t v) {
  asm volatile("cp.async.bulk.wait_group 0;" ::: "memory");
  __syncwarp();
  asm volatile("{\n.reg .pred e;\nelect.sync _|e, 0xffffffff;\n@e st.relaxed.gpu.global.u32 [%0], %1;\n}" :: "l"(flag), "r"(v) : "memory");
}
DEVI void e_expect(uint32_t bar, uint32_t bytes) { asm volatile(ELECT_PRE "mbarrier.arrive.expect_tx.shared::cta.b64 _, [%0], %1;\n}" :: "r"(bar), "r"(bytes) : "memory"); }
DEVI void e_bulk_g2s(uint32_t dst, const void* src, uint32_t bytes, uint32_t bar) {
  asm volatile(ELECT_PRE "cp.async.bulk.shared::cluster.global.mbarrier::complete_tx::bytes [%0], [%1], %2, [%3];\n}" :: "r"(dst), "l"(src), "r"(bytes), "r"(bar) : "memory");
}
DEVI uint32_t clock32() { uint32_t c; asm volatile("mov.u32 %0, %%clock;" : "=r"(c)); return c; }

template<int N, int TA, int TB> struct WG;
template<int TA, int TB> struct WG<32, TA, TB> {
  static __device__ __forceinline__ void ss(float* d, uint64_t da, uint64_t db, int sd) {
    asm volatile("{\n.reg .pred p;\nsetp.ne.b32 p, %18, 0;\n"
      "wgmma.mma_async.sync.aligned.m64n32k16.f32.bf16.bf16 {%0, %1, %2, %3, %4, %5, %6, %7, %8, %9, %10, %11, %12, %13, %14, %15}, %16, %17, p, 1, 1, %19, %20;\n}\n"
      : "+f"(d[0]), "+f"(d[1]), "+f"(d[2]), "+f"(d[3]), "+f"(d[4]), "+f"(d[5]), "+f"(d[6]), "+f"(d[7]), "+f"(d[8]), "+f"(d[9]), "+f"(d[10]), "+f"(d[11]), "+f"(d[12]), "+f"(d[13]), "+f"(d[14]), "+f"(d[15])
      : "l"(da), "l"(db), "r"(sd), "n"(TA), "n"(TB));
  }
  static __device__ __forceinline__ void rs(float* d, uint32_t a0, uint32_t a1, uint32_t a2, uint32_t a3, uint64_t db, int sd) {
    asm volatile("{\n.reg .pred p;\nsetp.ne.b32 p, %21, 0;\n"
      "wgmma.mma_async.sync.aligned.m64n32k16.f32.bf16.bf16 {%0, %1, %2, %3, %4, %5, %6, %7, %8, %9, %10, %11, %12, %13, %14, %15}, {%16, %17, %18, %19}, %20, p, 1, 1, %22;\n}\n"
      : "+f"(d[0]), "+f"(d[1]), "+f"(d[2]), "+f"(d[3]), "+f"(d[4]), "+f"(d[5]), "+f"(d[6]), "+f"(d[7]), "+f"(d[8]), "+f"(d[9]), "+f"(d[10]), "+f"(d[11]), "+f"(d[12]), "+f"(d[13]), "+f"(d[14]), "+f"(d[15])
      : "r"(a0), "r"(a1), "r"(a2), "r"(a3), "l"(db), "r"(sd), "n"(TB));
  }
};
template<int TA, int TB> struct WG<64, TA, TB> {
  static __device__ __forceinline__ void ss(float* d, uint64_t da, uint64_t db, int sd) {
    asm volatile("{\n.reg .pred p;\nsetp.ne.b32 p, %34, 0;\n"
      "wgmma.mma_async.sync.aligned.m64n64k16.f32.bf16.bf16 {%0, %1, %2, %3, %4, %5, %6, %7, %8, %9, %10, %11, %12, %13, %14, %15, %16, %17, %18, %19, %20, %21, %22, %23, %24, %25, %26, %27, %28, %29, %30, %31}, %32, %33, p, 1, 1, %35, %36;\n}\n"
      : "+f"(d[0]), "+f"(d[1]), "+f"(d[2]), "+f"(d[3]), "+f"(d[4]), "+f"(d[5]), "+f"(d[6]), "+f"(d[7]), "+f"(d[8]), "+f"(d[9]), "+f"(d[10]), "+f"(d[11]), "+f"(d[12]), "+f"(d[13]), "+f"(d[14]), "+f"(d[15]), "+f"(d[16]), "+f"(d[17]), "+f"(d[18]), "+f"(d[19]), "+f"(d[20]), "+f"(d[21]), "+f"(d[22]), "+f"(d[23]), "+f"(d[24]), "+f"(d[25]), "+f"(d[26]), "+f"(d[27]), "+f"(d[28]), "+f"(d[29]), "+f"(d[30]), "+f"(d[31])
      : "l"(da), "l"(db), "r"(sd), "n"(TA), "n"(TB));
  }
  static __device__ __forceinline__ void rs(float* d, uint32_t a0, uint32_t a1, uint32_t a2, uint32_t a3, uint64_t db, int sd) {
    asm volatile("{\n.reg .pred p;\nsetp.ne.b32 p, %37, 0;\n"
      "wgmma.mma_async.sync.aligned.m64n64k16.f32.bf16.bf16 {%0, %1, %2, %3, %4, %5, %6, %7, %8, %9, %10, %11, %12, %13, %14, %15, %16, %17, %18, %19, %20, %21, %22, %23, %24, %25, %26, %27, %28, %29, %30, %31}, {%32, %33, %34, %35}, %36, p, 1, 1, %38;\n}\n"
      : "+f"(d[0]), "+f"(d[1]), "+f"(d[2]), "+f"(d[3]), "+f"(d[4]), "+f"(d[5]), "+f"(d[6]), "+f"(d[7]), "+f"(d[8]), "+f"(d[9]), "+f"(d[10]), "+f"(d[11]), "+f"(d[12]), "+f"(d[13]), "+f"(d[14]), "+f"(d[15]), "+f"(d[16]), "+f"(d[17]), "+f"(d[18]), "+f"(d[19]), "+f"(d[20]), "+f"(d[21]), "+f"(d[22]), "+f"(d[23]), "+f"(d[24]), "+f"(d[25]), "+f"(d[26]), "+f"(d[27]), "+f"(d[28]), "+f"(d[29]), "+f"(d[30]), "+f"(d[31])
      : "r"(a0), "r"(a1), "r"(a2), "r"(a3), "l"(db), "r"(sd), "n"(TB));
  }
};
template<int TA, int TB> struct WG<128, TA, TB> {
  static __device__ __forceinline__ void ss(float* d, uint64_t da, uint64_t db, int sd) {
    asm volatile("{\n.reg .pred p;\nsetp.ne.b32 p, %66, 0;\n"
      "wgmma.mma_async.sync.aligned.m64n128k16.f32.bf16.bf16 {%0, %1, %2, %3, %4, %5, %6, %7, %8, %9, %10, %11, %12, %13, %14, %15, %16, %17, %18, %19, %20, %21, %22, %23, %24, %25, %26, %27, %28, %29, %30, %31, %32, %33, %34, %35, %36, %37, %38, %39, %40, %41, %42, %43, %44, %45, %46, %47, %48, %49, %50, %51, %52, %53, %54, %55, %56, %57, %58, %59, %60, %61, %62, %63}, %64, %65, p, 1, 1, %67, %68;\n}\n"
      : "+f"(d[0]), "+f"(d[1]), "+f"(d[2]), "+f"(d[3]), "+f"(d[4]), "+f"(d[5]), "+f"(d[6]), "+f"(d[7]), "+f"(d[8]), "+f"(d[9]), "+f"(d[10]), "+f"(d[11]), "+f"(d[12]), "+f"(d[13]), "+f"(d[14]), "+f"(d[15]), "+f"(d[16]), "+f"(d[17]), "+f"(d[18]), "+f"(d[19]), "+f"(d[20]), "+f"(d[21]), "+f"(d[22]), "+f"(d[23]), "+f"(d[24]), "+f"(d[25]), "+f"(d[26]), "+f"(d[27]), "+f"(d[28]), "+f"(d[29]), "+f"(d[30]), "+f"(d[31]), "+f"(d[32]), "+f"(d[33]), "+f"(d[34]), "+f"(d[35]), "+f"(d[36]), "+f"(d[37]), "+f"(d[38]), "+f"(d[39]), "+f"(d[40]), "+f"(d[41]), "+f"(d[42]), "+f"(d[43]), "+f"(d[44]), "+f"(d[45]), "+f"(d[46]), "+f"(d[47]), "+f"(d[48]), "+f"(d[49]), "+f"(d[50]), "+f"(d[51]), "+f"(d[52]), "+f"(d[53]), "+f"(d[54]), "+f"(d[55]), "+f"(d[56]), "+f"(d[57]), "+f"(d[58]), "+f"(d[59]), "+f"(d[60]), "+f"(d[61]), "+f"(d[62]), "+f"(d[63])
      : "l"(da), "l"(db), "r"(sd), "n"(TA), "n"(TB));
  }
  static __device__ __forceinline__ void rs(float* d, uint32_t a0, uint32_t a1, uint32_t a2, uint32_t a3, uint64_t db, int sd) {
    asm volatile("{\n.reg .pred p;\nsetp.ne.b32 p, %69, 0;\n"
      "wgmma.mma_async.sync.aligned.m64n128k16.f32.bf16.bf16 {%0, %1, %2, %3, %4, %5, %6, %7, %8, %9, %10, %11, %12, %13, %14, %15, %16, %17, %18, %19, %20, %21, %22, %23, %24, %25, %26, %27, %28, %29, %30, %31, %32, %33, %34, %35, %36, %37, %38, %39, %40, %41, %42, %43, %44, %45, %46, %47, %48, %49, %50, %51, %52, %53, %54, %55, %56, %57, %58, %59, %60, %61, %62, %63}, {%64, %65, %66, %67}, %68, p, 1, 1, %70;\n}\n"
      : "+f"(d[0]), "+f"(d[1]), "+f"(d[2]), "+f"(d[3]), "+f"(d[4]), "+f"(d[5]), "+f"(d[6]), "+f"(d[7]), "+f"(d[8]), "+f"(d[9]), "+f"(d[10]), "+f"(d[11]), "+f"(d[12]), "+f"(d[13]), "+f"(d[14]), "+f"(d[15]), "+f"(d[16]), "+f"(d[17]), "+f"(d[18]), "+f"(d[19]), "+f"(d[20]), "+f"(d[21]), "+f"(d[22]), "+f"(d[23]), "+f"(d[24]), "+f"(d[25]), "+f"(d[26]), "+f"(d[27]), "+f"(d[28]), "+f"(d[29]), "+f"(d[30]), "+f"(d[31]), "+f"(d[32]), "+f"(d[33]), "+f"(d[34]), "+f"(d[35]), "+f"(d[36]), "+f"(d[37]), "+f"(d[38]), "+f"(d[39]), "+f"(d[40]), "+f"(d[41]), "+f"(d[42]), "+f"(d[43]), "+f"(d[44]), "+f"(d[45]), "+f"(d[46]), "+f"(d[47]), "+f"(d[48]), "+f"(d[49]), "+f"(d[50]), "+f"(d[51]), "+f"(d[52]), "+f"(d[53]), "+f"(d[54]), "+f"(d[55]), "+f"(d[56]), "+f"(d[57]), "+f"(d[58]), "+f"(d[59]), "+f"(d[60]), "+f"(d[61]), "+f"(d[62]), "+f"(d[63])
      : "r"(a0), "r"(a1), "r"(a2), "r"(a3), "l"(db), "r"(sd), "n"(TB));
  }
};

constexpr int S_ = 2048;
constexpr int CONV_CTAS = 20;
constexpr int CONV_CH = 336;
constexpr int CV_NT = 8;
constexpr int CV_ODD_OFF = 2080;
constexpr int CV_COPY_OFF = 4160;
constexpr int CV_TAB = 8320;
constexpr int CV_KPAD = 384;
constexpr int CV_KROW = 4096 + CV_KPAD;
constexpr int CV_SLOT = CV_TAB + CV_KROW;
constexpr int CV_RAW_BLK = 33;
constexpr int CV_RAWQ = 16 * CV_RAW_BLK * 16;
constexpr int CV_RAW_BYTES = 4 * CV_RAWQ;
constexpr int CV_RW = 4096 + 128;
constexpr int CV_RBYTES = 4 * CV_RW;
constexpr int CV_OFF_RAWK = CV_NT * CV_SLOT;
constexpr int CV_OFF_RAWV = CV_OFF_RAWK + CV_RAW_BYTES;
constexpr int CV_OFF_R = CV_OFF_RAWV + CV_RAW_BYTES;
constexpr int CV_OFF_BAR = CV_OFF_R + 2 * CV_RBYTES;
constexpr int CV_SMEM = CV_OFF_BAR + 512 + 128;
static_assert(CV_OFF_RAWK % 128 == 0 && CV_OFF_RAWV % 128 == 0 && CV_SLOT % 128 == 0, "align");
#define CV_RB 56
#define CV_RM 224

struct ConvParams {
  const __nv_bfloat16* k; const __nv_bfloat16* v; const __nv_bfloat16* shift_k; const __nv_bfloat16* ssm_k; const __nv_bfloat16* ssm_D;
  __nv_bfloat16* yT; uint32_t* yflag; uint32_t* epoch; uint32_t* readers; uint32_t* ticket; long long* dbg;
};

template<int I, int G, int IE> struct ConvMma {
  static DEVI void run(float* d, const uint32_t* a, uint32_t db) {
    if (G * 32 + 32 > 16 * I)
      WG<32, 0, 0>::rs(d + G * 16, a[4 * I], a[4 * I + 1], a[4 * I + 2], a[4 * I + 3], ((uint64_t)8 << 32) | (db + (uint32_t)(int)(G * 32 - 16 * I)), I > 0);
    ConvMma<G == 7 ? I + 1 : I, G == 7 ? 0 : G + 1, IE>::run(d, a, db);
  }
};
template<int IE> struct ConvMma<IE, 0, IE> { static DEVI void run(float*, const uint32_t*, uint32_t) {} };

DEVI void conv_load_a(uint32_t* a, int i, uint32_t pO, uint32_t pE) {
  a[4 * i + 0] = lds32(pO + 128 * i);
  a[4 * i + 1] = lds32(pO + 128 * i + 64);
  a[4 * i + 2] = lds32(pE + 128 * i);
  a[4 * i + 3] = lds32(pE + 128 * i + 64);
}

__global__ void __launch_bounds__(384, 1) conv_kernel(const __grid_constant__ CUtensorMap tmK, const __grid_constant__ CUtensorMap tmV, ConvParams p) {
  extern __shared__ __align__(1024) unsigned char smem_raw[];
  const uint32_t sb = __shfl_sync(0xffffffffu, (smem_u32(smem_raw) + 127) & ~127u, 0);
  const int tid = threadIdx.x, lane = tid & 31;
  const int wid = __shfl_sync(0xffffffffu, tid >> 5, 0), wgi = wid >> 2, warp = wid & 3;
  const int c0 = (int)(blockIdx.x * CONV_CH) / CONV_CTAS, c1 = (int)((blockIdx.x + 1) * CONV_CH) / CONV_CTAS;
  const int nch = c1 - c0;
  const int cs = (c0 + 7) & ~7, nhi = c1 - cs;
  auto chan = [&](int lc) { return lc < nhi ? cs + lc : c0 + lc - nhi; };
  const uint32_t bar = sb + CV_OFF_BAR;
  const uint32_t TFULL = bar, TEMPTY = bar + 64, KFULL = bar + 128, RAWFULL = bar + 192, KRDY = bar + 256;
  if (wid == 8) {
    e_pftm(&tmK); e_pftm(&tmV);
    if (lane == 0) {
      #pragma unroll
      for (int i = 0; i < CV_NT; i++) { mbar_init(TFULL + 8 * i, 4); mbar_init(TEMPTY + 8 * i, 4); mbar_init(KFULL + 8 * i, 1); mbar_init(KRDY + 8 * i, 1); }
      #pragma unroll
      for (int i = 0; i < 4; i++) mbar_init(RAWFULL + 8 * i, 1);
    }
    __syncwarp();
    if (lane < 4) mbar_expect_tx(RAWFULL + 8 * lane, 2 * CV_RAWQ);
    if (lane < CV_NT) mbar_expect_tx(KFULL + 8 * lane, 4096);
    __syncwarp();
    e_tma3d(sb + CV_OFF_RAWK, &tmK, cs, -1, 0, RAWFULL);
    e_tma3d(sb + CV_OFF_RAWV, &tmV, cs, -1, 0, RAWFULL);
  }
  if (wid >= 9) {
    const int z = tid - 288;
    if (z < CV_NT * 4) sts128(sb + (z >> 2) * CV_SLOT + ((z >> 1) & 1) * CV_COPY_OFF + (z & 1) * CV_ODD_OFF, 0, 0, 0, 0);
    #pragma unroll
    for (int i = 0; i < 2; i++) {
      const int u = z + 96 * i;
      sts128(sb + (u / (CV_KPAD / 16)) * CV_SLOT + CV_TAB + (u % (CV_KPAD / 16)) * 16, 0, 0, 0, 0);
    }
    if (z < 64) sts128(sb + CV_OFF_R + (z >> 3) * CV_RW + (z & 7) * 16, 0, 0, 0, 0);
  }
  __syncthreads();

  if (wgi == 2) {
    reg_dec<CV_RB>();
    const int bt = tid - 256;
    if (warp > 0) {
      const uint32_t t0 = clock32();
      while (clock32() - t0 < 150u * warp) {}
      e_tma3d(sb + CV_OFF_RAWK + warp * CV_RAWQ, &tmK, cs, 32 * warp - 1, 0, RAWFULL + 8 * warp);
      e_tma3d(sb + CV_OFF_RAWV + warp * CV_RAWQ, &tmV, cs, 32 * warp - 1, 0, RAWFULL + 8 * warp);
    }
    e_bulk_g2s(sb + warp * CV_SLOT + CV_TAB + CV_KPAD, p.ssm_k + (size_t)(cs + warp) * S_, 4096, KFULL + 8 * warp);
    e_bulk_g2s(sb + (warp + 4) * CV_SLOT + CV_TAB + CV_KPAD, p.ssm_k + (size_t)(cs + 4 + warp) * S_, 4096, KFULL + 8 * warp + 32);
    uint32_t rawph = 0;
    const int nq = ((c1 - 1) >> 2) - (c0 >> 2) + 1, nqhi = ((c1 - 1) >> 2) - (cs >> 2) + 1;
    #pragma unroll 1
    for (int qi = 0; qi < nq; qi++) {
      const int q = qi < nqhi ? (cs >> 2) + qi : (c0 >> 2) + qi - nqhi;
      const int qn = qi + 1 < nqhi ? q + 1 : (c0 >> 2) + qi + 1 - nqhi;
      uint32_t sh[2][4];
      {
        const uint4* sp = reinterpret_cast<const uint4*>(p.shift_k + (size_t)q * 16);
        uint4 a = __ldg(sp), b = __ldg(sp + 1);
        sh[0][0] = prmt(a.x, a.z, 0x5410); sh[0][1] = prmt(a.x, a.z, 0x7632); sh[0][2] = prmt(a.y, a.w, 0x5410); sh[0][3] = prmt(a.y, a.w, 0x7632);
        sh[1][0] = prmt(b.x, b.z, 0x5410); sh[1][1] = prmt(b.x, b.z, 0x7632); sh[1][2] = prmt(b.y, b.w, 0x5410); sh[1][3] = prmt(b.y, b.w, 0x7632);
      }
      const int lc0 = qi < nqhi ? 4 * q - cs : 4 * q - c0 + nhi;
      uint32_t um = 0;
      #pragma unroll
      for (int c = 0; c < 4; c++) {
        const int lc = lc0 + c;
        if (4 * q + c >= c0 && 4 * q + c < c1) {
          um |= 1u << c;
          if (lc >= CV_NT) mbar_wait(TEMPTY + 8 * (lc & 7), ((lc >> 3) - 1) & 1);
        }
      }
      const bool kth = ((um >> warp) & 1) != 0;
      const float dv = __bfloat162float(p.ssm_D[4 * q + warp]);
      if (qi == 0 || qi == nqhi || (q & 1) == 0) { mbar_wait(RAWFULL + 8 * warp, rawph); rawph ^= 1; }
      const uint32_t kb = sb + CV_OFF_RAWK + warp * CV_RAWQ + lane * 16 + (q & 1) * 8, vb = kb + CV_RAW_BYTES;
      const uint32_t tw = sb + 16 + bt * 16;
      auto ldk = [&](int r) { return lds64(kb + (r & 15) * (CV_RAW_BLK * 16) + (r >= 0 ? 16 : 0)); };
      auto ldv = [&](int r) { return lds64(vb + (r & 15) * (CV_RAW_BLK * 16) + (r >= 0 ? 16 : 0)); };
      uint2 k3 = ldk(-4), k2 = ldk(-3), k1 = ldk(-2), k0;
      uint2 up;
      uint32_t w[2][4][4];
      #pragma unroll
      for (int r = -1; r < 16; r++) {
        k0 = ldk(r);
        uint2 vv = ldv(r);
        uint2 u;
        u.x = hmul2(hfma2(k0.x, sh[0][0], hfma2(k1.x, sh[0][1], hfma2(k2.x, sh[0][2], hmul2(k3.x, sh[0][3])))), vv.x);
        u.y = hmul2(hfma2(k0.y, sh[1][0], hfma2(k1.y, sh[1][1], hfma2(k2.y, sh[1][2], hmul2(k3.y, sh[1][3])))), vv.y);
        k3 = k2; k2 = k1; k1 = k0;
        if (r >= 0) {
          const int cp = r & 1, wi = (r >> 1) & 3;
          w[cp][0][wi] = prmt(u.x, up.x, 0x5410); w[cp][1][wi] = prmt(u.x, up.x, 0x7632);
          w[cp][2][wi] = prmt(u.y, up.y, 0x5410); w[cp][3][wi] = prmt(u.y, up.y, 0x7632);
          if ((r & 7) == 6 || (r & 7) == 7) {
            const uint32_t off = cp * CV_COPY_OFF + (r >> 3) * CV_ODD_OFF;
            #pragma unroll
            for (int c = 0; c < 4; c++) if ((um >> c) & 1) sts128(tw + ((lc0 + c) & 7) * CV_SLOT + off, w[cp][c][0], w[cp][c][1], w[cp][c][2], w[cp][c][3]);
          }
        }
        up = u;
      }
      if (qi == 0) fence_async_smem();
      __syncwarp();
      if (lane < 4 && ((um >> lane) & 1)) mbar_arrive(TFULL + 8 * ((lc0 + lane) & 7));
      if (qi + 1 < nq && (qn >> 1) != (q >> 1)) {
        e_expect(RAWFULL + 8 * warp, 2 * CV_RAWQ);
        e_tma3d(sb + CV_OFF_RAWK + warp * CV_RAWQ, &tmK, (qn >> 1) * 8, 32 * warp - 1, 0, RAWFULL + 8 * warp);
        e_tma3d(sb + CV_OFF_RAWV + warp * CV_RAWQ, &tmV, (qn >> 1) * 8, 32 * warp - 1, 0, RAWFULL + 8 * warp);
      }
      if (kth) {
        const int lc = lc0 + warp;
        const uint32_t kr = sb + (lc & 7) * CV_SLOT + CV_TAB + CV_KPAD;
        mbar_wait(KFULL + 8 * (lc & 7), (lc >> 3) & 1);
        if (lane == 0) {
          const uint32_t w0 = lds32(kr);
          sts32(kr, (pack_bf16(bf_lo(w0) + dv, 0.f) & 0xffffu) | (w0 & 0xffff0000u));
          fence_async_smem();
          mbar_arrive(KRDY + 8 * (lc & 7));
        }
        __syncwarp();
      }
    }
  } else {
    reg_inc<CV_RM>();
    const int g = lane >> 2, t = lane & 3;
    const int dl = (g >> 1) - t;
    const uint32_t cpy = sb + (g & 1) * CV_COPY_OFF + 16 + 16 * warp;
    const uint32_t offE = __shfl_sync(0xffffffffu, cpy + (dl >= 0 ? 4 * dl : CV_ODD_OFF - 16 + 4 * (4 + dl)), lane);
    const uint32_t offO = __shfl_sync(0xffffffffu, cpy + (dl >= 0 ? CV_ODD_OFF + 4 * dl : 4 * (4 + dl)), lane);
    const uint32_t rb = sb + CV_OFF_R + wgi * CV_RBYTES;
    const uint32_t rw = __shfl_sync(0xffffffffu, rb + warp * CV_RW + (2 * warp + lane) * 16, lane);
    const uint32_t rr = __shfl_sync(0xffffffffu, rb + (warp * 64 + lane) * 16, lane);
    float d[128];
    uint32_t a[64];
    if (wgi == 1) bar_arrive(1, 256);
    uint32_t E = 0;
    if (tid == 0) E = ld_relaxed(p.epoch) + 1;
    #pragma unroll
    for (int i = 0; i < 64; i++) a[i] = 0;
    #pragma unroll 1
    for (int lc = wgi - 4; lc < nch; lc += 2) {
      const uint32_t krow = sb + (lc & 7) * CV_SLOT + CV_TAB + CV_KPAD;
      const uint32_t db = (((krow - 16) & 0x3FFFF) >> 4) | (1u << 16);
      const bool real = lc >= 0, more = lc + 2 >= 0 && lc + 2 < nch;
      const uint32_t ns = ((lc + 2) & 7) * CV_SLOT;
      if (real) bar_sync(1 + wgi, 256);
      if (real || lc < -2) {
        wg_fence();
        ConvMma<0, 0, 16>::run(d, a, db);
        wg_commit();
      }
      if (real && lc + 1 < nch) bar_arrive(2 - wgi, 256);
      if (more) {
        mbar_wait(TFULL + 8 * ((lc + 2) & 7), ((lc + 2) >> 3) & 1);
        mbar_wait(KRDY + 8 * ((lc + 2) & 7), ((lc + 2) >> 3) & 1);
      }
      wg_wait<0>();
      #pragma unroll
      for (int b = 0; b < 8; b++) {
        conv_load_a(a, b, offO + ns, offE + ns);
        uint32_t o[4];
        #pragma unroll
        for (int m = 0; m < 4; m++) {
          const int jj = 4 * b + m;
          o[m] = jj == 0 ? pack_bf16(d[0], d[1]) : pack_bf16(d[4 * jj] + d[4 * jj - 2], d[4 * jj + 1] + d[4 * jj - 1]);
        }
        stsm4t(rw + b * 512, o[0], o[1], o[2], o[3]);
      }
      bar_sync(3 + wgi, 128);
      uint4 y0 = lds128(rr), y1 = lds128(rr + 512);
      #pragma unroll
      for (int w = 1; w < 4; w++) {
        uint4 x0 = lds128(rr + w * CV_RW), x1 = lds128(rr + w * CV_RW + 512);
        y0.x = hadd2(y0.x, x0.x); y0.y = hadd2(y0.y, x0.y); y0.z = hadd2(y0.z, x0.z); y0.w = hadd2(y0.w, x0.w);
        y1.x = hadd2(y1.x, x1.x); y1.y = hadd2(y1.y, x1.y); y1.z = hadd2(y1.z, x1.z); y1.w = hadd2(y1.w, x1.w);
      }
      #pragma unroll
      for (int i = 8; i < 16; i++) conv_load_a(a, i, offO + ns, offE + ns);
      if (real) {
        uint4* yo = reinterpret_cast<uint4*>(p.yT + (size_t)chan(lc) * S_) + warp * 64 + lane;
        yo[0] = y0; yo[32] = y1;
      } else bar_sync(3 + wgi, 128);
      __syncwarp();
      if (more) e_arrive(TEMPTY + 8 * ((lc + 2) & 7));
      if (warp == 1 && real && lc + CV_NT < nch) {
        e_expect(KFULL + 8 * (lc & 7), 4096);
        e_bulk_g2s(krow, p.ssm_k + (size_t)chan(lc + CV_NT) * S_, 4096, KFULL + 8 * (lc & 7));
      }
    }
    bar_sync(6, 256);
    if (wid == 0) {
      uint32_t tk = 0;
      if (lane == 0) {
        __threadfence();
        st_relaxed(p.yflag + blockIdx.x, E);
        tk = atomicInc(p.ticket, CONV_CTAS - 1);
      }
      if (__shfl_sync(0xffffffffu, tk, 0) == CONV_CTAS - 1) {
        E = __shfl_sync(0xffffffffu, E, 0);
        for (int it = 0; it < (1 << 20); it++) {
          bool ok = true;
          #pragma unroll
          for (int i = 0; i < 4; i++) ok = ok && (lane + 32 * i >= 112 || ld_relaxed(p.readers + lane + 32 * i) == E);
          if (__all_sync(0xffffffffu, ok)) break;
        }
        if (lane == 0) st_relaxed(p.epoch, E);
      }
    }
  }
}

constexpr int G_CTAS = 112;
constexpr int SLOT = 16384;
constexpr int G_OFF_MISC = 13 * SLOT;
constexpr int G_OFF_ROWC = G_OFF_MISC;
constexpr int G_OFF_CS = G_OFF_ROWC + 2048;
constexpr int G_OFF_ZST = G_OFF_CS + 1024;
constexpr int G_OFF_TAB = G_OFF_ZST + 1024;
constexpr int G_OFF_KR = G_OFF_TAB + CV_TAB;
constexpr int G_OFF_BAR = G_OFF_KR + CV_KROW;
constexpr int B_XF = 0;
constexpr int B_WF = B_XF + 7;
constexpr int B_HF = B_WF + 14;
constexpr int B_X2F = B_HF + 4;
constexpr int B_YF = B_X2F + 1;
constexpr int B_OF = B_YF + 1;
constexpr int B_F2 = B_OF + 4;
constexpr int B_ZFREE = B_F2 + 6;
constexpr int B_HFREE = B_ZFREE + 1;
constexpr int B_CVF = B_HFREE + 2;
constexpr int B_CVR = B_CVF + 1;
constexpr int B_RA = B_CVR + 1;
constexpr int B_HR = B_RA + 6;
constexpr int B_RB = B_HR + 4;
constexpr int B_OR = B_RB + 6;
constexpr int B_WR = B_OR + 3 - 4;
constexpr int B_WR3 = B_WR + 8;
constexpr int B_PRE = B_WR3 + 4;
constexpr int B_ZST = B_PRE + 1;
constexpr int B_S5 = B_PRE + 2;
constexpr int B_XR = B_PRE + 3;
constexpr int B_YR = B_PRE + 4;
constexpr int B_PRE1 = B_PRE + 5;
constexpr int B_ZSTG = B_PRE + 6;
constexpr int B_HSTG = B_ZSTG + 2;
constexpr int B_OSTG = B_ZSTG + 4;
constexpr int B_ZPUB = B_ZSTG + 6;
constexpr int B_YD = B_ZPUB + 2;
constexpr int B_NUM = B_YD + 1;
constexpr int G_SMEM = G_OFF_BAR + B_NUM * 8 + 1024;

struct GemmParams {
  const __nv_bfloat16* x; const __nv_bfloat16* w_in; const __nv_bfloat16* b_sp;
  const __nv_bfloat16* k; const __nv_bfloat16* v; const __nv_bfloat16* shift_k; const __nv_bfloat16* ssm_k; const __nv_bfloat16* ssm_D;
  unsigned char* utab; __nv_bfloat16* yT; uint32_t* uflag;
  uint4* xstat; uint2* csum; uint2* zpart; uint32_t* zflag; uint32_t* hflag; uint32_t* yflag; uint32_t* epoch; uint32_t* readers;
  long long* dbg;
};
struct GemmMaps { CUtensorMap x, win, wsp, z2, hld, hst, wout, y, out; };

DEVI void fence_async_global() { asm volatile("fence.proxy.async.global;" ::: "memory"); }
DEVI uint4 ld_vol4(const uint4* p) { uint4 v; asm volatile("ld.relaxed.gpu.global.v4.u32 {%0,%1,%2,%3}, [%4];" : "=r"(v.x), "=r"(v.y), "=r"(v.z), "=r"(v.w) : "l"(p) : "memory"); return v; }
DEVI uint2 ld_vol2(const uint2* p) { uint2 v; asm volatile("ld.relaxed.gpu.global.v2.u32 {%0,%1}, [%2];" : "=r"(v.x), "=r"(v.y) : "l"(p) : "memory"); return v; }
DEVI void st_vol4(uint4* p, uint32_t a, uint32_t b, uint32_t c, uint32_t d) { asm volatile("st.relaxed.gpu.global.v4.u32 [%0], {%1,%2,%3,%4};" :: "l"(p), "r"(a), "r"(b), "r"(c), "r"(d) : "memory"); }
DEVI void st_vol2(uint2* p, uint32_t a, uint32_t b) { asm volatile("st.relaxed.gpu.global.v2.u32 [%0], {%1,%2};" :: "l"(p), "r"(a), "r"(b) : "memory"); }

DEVI void mma16816(float* c, uint32_t a0, uint32_t a1, uint32_t a2, uint32_t a3, uint32_t b0, uint32_t b1) {
  asm volatile("mma.sync.aligned.m16n8k16.row.col.f32.bf16.bf16.f32 {%0,%1,%2,%3}, {%4,%5,%6,%7}, {%8,%9}, {%0,%1,%2,%3};"
    : "+f"(c[0]), "+f"(c[1]), "+f"(c[2]), "+f"(c[3]) : "r"(a0), "r"(a1), "r"(a2), "r"(a3), "r"(b0), "r"(b1));
}
template<int N> DEVI void pin(float* a) {
  #pragma unroll
  for (int i = 0; i < N; i++) asm volatile("" : "+f"(a[i]) :: "memory");
}
#define G_RP 56
#define G_RC 224
#define PACE 400
constexpr int SPIN_LIM = 1 << 20;
constexpr uint64_t DESC_K = ((uint64_t)1 << 62) | ((uint64_t)64 << 32) | ((uint64_t)1 << 16);
constexpr uint64_t DESC_N = ((uint64_t)1 << 62) | ((uint64_t)64 << 32) | ((uint64_t)512 << 16);
DEVI uint64_t dk(uint32_t a) { return DESC_K | (uint64_t)((a & 0x3FFFF) >> 4); }
DEVI uint64_t dn(uint32_t a) { return DESC_N | (uint64_t)((a & 0x3FFFF) >> 4); }
DEVI int wslot(int q) { return q < 6 ? 7 + q : 7 + ((q - 6) & 3); }
DEVI int aslot(int s) { return (0xA98720 >> (4 * s)) & 15; }
DEVI int bslot(int s) { return (0xB65431 >> (4 * s)) & 15; }
DEVI int oslot(int p) { return (0x695847C >> (4 * p)) & 15; }

#define GT(k) do {} while (0)
#define TR(n)
#define TW(k, n)

constexpr float GELU_C0 = 0.7978845608028654f, GELU_C1 = 0.7978845608028654f * 0.044715f;

__global__ void __launch_bounds__(384, 1) gemm_kernel(const __grid_constant__ GemmMaps tm, GemmParams p) {
  extern __shared__ __align__(1024) unsigned char smem_raw[];
  const uint32_t sb = __shfl_sync(0xffffffffu, (smem_u32(smem_raw) + 1023) & ~1023u, 0);
  const int tid = threadIdx.x, lane = tid & 31;
  const int wid = __shfl_sync(0xffffffffu, tid >> 5, 0);
  const int tau = blockIdx.x, ti = tau / 7, tj = tau - 7 * ti;
  const int cbase = tau & ~15;
  const int rlo = max(7 * ti, cbase), rhi = min(7 * ti + 7, cbase + 16);
  const int r0 = rlo - cbase, nrow = rhi - rlo, myr = tau - rlo;
  const int myc = (tau & 15) >= 14 ? 2 : (tau & 15) >= 7 ? 1 : 0, cf = (tau & 15) - 7 * myc, ncol = cf < 2 ? 3 : 2;
  const uint16_t rmask = (uint16_t)(((1u << nrow) - 1) << r0);
  const uint16_t cmask = (uint16_t)((ncol == 3 ? 0x4081u : 0x81u) << cf);
  const uint32_t bar = sb + G_OFF_BAR;
  auto BA = [&](int i) { return bar + 8 * i; };
  const uint32_t rm = nrow == 1 ? 0u : nrow == 2 ? 0x101010u : nrow == 3 ? 0x210210u : nrow == 4 ? 0x103210u : nrow == 5 ? 0x043210u : 0x543210u;
  auto rdst = [&](int k) { return r0 + ((rm >> (4 * k)) & 15); };
  auto cdst = [&](int k) { return cf + 7 * (ncol == 2 ? (k & 1) : (int)((0x924924924ull >> (2 * k)) & 3)); };
  asm volatile("griddepcontrol.launch_dependents;");
  if (wid == 11) {
    cluster_arrive_relaxed();
  }
  uint4 pv[7];
  const int xrl = 4 * (wid - 3) + (lane >> 3), xrow = 128 * ti + min(19 * tj + xrl, 127);
  if (wid >= 3 && wid < 8) {
    const uint4* xp = reinterpret_cast<const uint4*>(p.x + (size_t)xrow * 448) + (lane & 7);
    #pragma unroll
    for (int r = 0; r < 7; r++) pv[r] = __ldg(xp + 8 * r);
  } else {
    auto init_range = [&](int first, int n, uint32_t cnt) {
      #pragma unroll
      for (int i = 0; i < 21; i++) if (i < n) mbar_init(BA(first + i), cnt);
    };
    if (wid == 9) e_pftm(&tm.win);
    if (wid == 8) e_pftm(&tm.x);
    if (lane == 0) {
      if (wid < 2) init_range(21 * wid, 21, 1);
      else if (wid == 2) init_range(B_RA, 10, 2 * nrow);
      else if (wid == 10) init_range(B_RB, 13, 2 * ncol);
      else if (wid == 9) { init_range(B_WR3, 4, 3 * ncol); init_range(B_PRE, 6, 2); }
      else if (wid == 8) init_range(B_ZSTG, 9, 4);
    }
    __syncwarp();
    if (wid < 2) {
      const int i = 21 * wid + lane;
      if (lane < 21 && (i < B_ZFREE || i == B_CVF)) mbar_expect_tx(BA(i), i == B_CVF ? CV_TAB + 4096 : i > B_OF ? 2 * SLOT : SLOT);
    }
    if (wid == 2 && lane < CV_KPAD / 16) { sts128(sb + G_OFF_KR + lane * 16, 0, 0, 0, 0); fence_async_smem(); }
  }
  asm volatile("fence.mbarrier_init.release.cluster;" ::: "memory");
  __syncwarp();
  TR(T2);
  if (wid != 11) cluster_arrive_relaxed();
  uint32_t E = 0;

  if (wid >= 8) {
    reg_dec<G_RP>();
    if (wid < 10) {
      cluster_wait();
      const uint32_t tstart = clock32();
      if (wid == 8) {
        #pragma unroll 1
        for (int b = myr; b < 7; b += nrow) {
          while (clock32() - tstart < (uint32_t)(PACE * b)) {}
          e_tma2d_mc(sb + b * SLOT, &tm.x, 64 * b, 128 * ti, BA(B_XF + b), rmask);
        }
      } else {
        #pragma unroll 1
        for (int q = myc; q < 6; q += ncol) {
          while (clock32() - tstart < (uint32_t)(PACE * q)) {}
          e_tma3d_mc(sb + (7 + q) * SLOT, &tm.win, 0, 64 * q, 14 + 2 * tj, BA(B_WF + q), cmask);
        }
      }
      E = ld_relaxed(p.epoch) + 1;
      if (wid == 8) {
        e_pftm(&tm.wsp); e_pftm(&tm.hld); e_pftm(&tm.z2);
        mbar_wait(BA(B_WF + 9), 0);
        #pragma unroll 1
        for (int kp = myr; kp < 12; kp += nrow) e_pf2d(&tm.wsp, 64 * kp, 128 * ti);
        mbar_wait(BA(B_ZSTG), 0);
        e_store3d(&tm.z2, sb + 11 * SLOT, 0, 128 * ti, 2 * tj);
        mbar_wait(BA(B_ZSTG + 1), 0);
        e_store3d(&tm.z2, sb + 12 * SLOT, 0, 128 * ti + 64, 2 * tj);
        bulk_wait<0>();
        __syncwarp();
        if (lane < 2) st_relaxed(p.zflag + tj * 32 + 2 * ti + lane, E);
        e_arrive(BA(B_ZFREE));
        if (lane == 0) { GT(6); }
        {
          int s = 0; uint32_t ph = 0;
          #pragma unroll 1
          for (int k = 0; k < 32; k++) {
            if (((rm >> (4 * s)) & 15) == myr) {
              mbar_wait(BA(B_RA + s), ph);
              e_tma2d_mc(sb + aslot(s) * SLOT, &tm.wsp, 64 * k, 128 * ti, BA(B_F2 + s), rmask);
              if (k + 12 < 32) e_pf2d(&tm.wsp, 64 * (k + 12), 128 * ti);
            }
            if (++s == 6) { s = 0; ph ^= 1; }
          }
        }
        uint32_t ready = 0;
        #pragma unroll 1
        for (int k = 0; k < 14; k++) {
          if (((rm >> (4 * (k & 3))) & 15) == myr) {
            if (((ready >> (k & ~1)) & 3) != 3) {
              #pragma unroll 1
              for (int it = 0; ((ready >> (k & ~1)) & 3) != 3 && it < SPIN_LIM; it++)
                ready = __ballot_sync(0xffffffffu, lane < 14 && ld_relaxed(p.hflag + ti * 16 + lane) == E);
              fence_async_global();
            }
            mbar_wait(BA(B_HR + (k & 3)), (k >> 2) & 1);
            e_tma2d_mc(sb + (k & 3) * SLOT, &tm.hld, 64 * k, 128 * ti, BA(B_HF + (k & 3)), rmask);
          }
        }
      } else {
        const int q0 = 6 + myc;
        e_pftm(&tm.wout); e_pftm(&tm.y);
        while (clock32() - tstart < (uint32_t)(PACE * 6)) {}
        #pragma unroll 1
        for (int q = q0; q < 14; q += ncol) e_pf3d(&tm.win, 0, q == 6 ? 384 : 64 * (q - 7), q == 6 ? 14 + 2 * tj : 2 * tj);
        if (lane == 0) st_relaxed(p.readers + tau, E);
        #pragma unroll 1
        for (int q = q0; q < 14; q += ncol) {
          mbar_wait(BA(q < 10 ? B_WR3 + q - 6 : B_WR + q - 6), 0);
          e_tma3d_mc(sb + wslot(q) * SLOT, &tm.win, 0, q == 6 ? 384 : 64 * (q - 7), q == 6 ? 14 + 2 * tj : 2 * tj, BA(B_WF + q), cmask);
        }
        uint32_t ready = 0, ph = 0;
        int s = myc;
        #pragma unroll 1
        for (int k = myc; k < 32; k += ncol) {
          if (!((ready >> k) & 1)) {
            #pragma unroll 1
            for (int it = 0; !((ready >> k) & 1) && it < SPIN_LIM; it++)
              ready = __ballot_sync(0xffffffffu, ld_relaxed(p.zflag + tj * 32 + lane) == E);
            fence_async_global();
          }
          mbar_wait(BA(B_RB + s), ph);
          e_tma3d_mc(sb + bslot(s) * SLOT, &tm.z2, 0, 64 * k, 2 * tj, BA(B_F2 + s), cmask);
          if (k < 3 && lane == 0) { GT(2); }
          if (k >= 6 && k < 6 + ncol) {
            mbar_wait(BA(B_ZFREE), 0);
            e_tma2d(sb + oslot(0) * SLOT, &tm.wout, 64 * tj, 0, BA(B_OF));
          }
          s += ncol; if (s >= 6) { s -= 6; ph ^= 1; }
        }
        #pragma unroll 1
        for (int g3 = myc; g3 < 3; g3 += ncol) {
          mbar_wait(BA(B_OR + g3), 0);
          e_tma2d_mc(sb + oslot(1 + 2 * g3) * SLOT, &tm.wout, 64 * tj, 128 * (1 + 2 * g3), BA(B_OF + 1 + g3), cmask);
          e_tma2d_mc(sb + oslot(2 + 2 * g3) * SLOT, &tm.wout, 64 * tj, 128 * (2 + 2 * g3), BA(B_OF + 1 + g3), cmask);
        }
        mbar_wait(BA(B_XR), 0);
        e_tma2d(sb + oslot(0) * SLOT, &tm.x, 64 * tj, 128 * ti, BA(B_X2F));
        const int cha = 64 * tj + lane, chb = cha + 32;
        const uint32_t* fa = p.yflag + (cha < CONV_CH ? (cha * CONV_CTAS + CONV_CTAS - 1) / CONV_CH : 32 + cha - CONV_CH);
        const uint32_t* fb = p.yflag + (chb < CONV_CH ? (chb * CONV_CTAS + CONV_CTAS - 1) / CONV_CH : 32 + chb - CONV_CH);
        bool ok = false;
        #pragma unroll 1
        for (int it = 0; !ok && it < SPIN_LIM; it++) ok = __all_sync(0xffffffffu, ld_relaxed(fa) == E && ld_relaxed(fb) == E);
        __threadfence();
        if (lane == 0) { GT(9); }
        fence_async_global();
        mbar_wait(BA(B_YR), 0);
        e_tma3d(sb + oslot(1) * SLOT, &tm.y, 0, 64 * tj, 2 * ti, BA(B_YF));
      }
    } else {
      const int aw = wid - 10, at = tid - 320;
      E = ld_relaxed(p.epoch) + 1;
      cluster_wait();
      e_pftm(&tm.hst); e_pftm(&tm.out);
      float cs[8] = {0.f, 0.f, 0.f, 0.f, 0.f, 0.f, 0.f, 0.f};
      const int wr = 32 * aw + lane;
      auto cs_publish = [&](int col0) {
        #pragma unroll
        for (int s3 = 0; s3 < 3; s3++) {
          const int o = 1 << s3, h = 4 >> s3;
          const bool up = lane & o;
          #pragma unroll
          for (int c = 0; c < 4; c++) if (c < h) {
            const float send = up ? cs[c] : cs[c + h], keep = up ? cs[c + h] : cs[c];
            cs[c] = keep + __shfl_xor_sync(0xffffffffu, send, o);
          }
        }
        cs[0] += __shfl_xor_sync(0xffffffffu, cs[0], 8);
        cs[0] += __shfl_xor_sync(0xffffffffu, cs[0], 16);
        const int col = (lane & 1) * 4 + (lane & 2) + ((lane >> 2) & 1);
        if (lane < 8) st_vol2(p.csum + (size_t)aw * 1792 + col0 + col, __float_as_uint(cs[0]), E);
        #pragma unroll
        for (int c = 0; c < 8; c++) cs[c] = 0.f;
      };
      auto ok4 = [&](const uint4& v) { return v.y == E && v.w == E; };
      auto gather_cs = [&](const uint4* s0, uint4 a, uint4 b, uint32_t dst) {
        #pragma unroll 1
        for (int it = 0; !(ok4(a) && ok4(b)) && it < SPIN_LIM; it++) { a = ld_vol4(s0); b = ld_vol4(s0 + 896); }
        sts64(dst + at * 8, __float_as_uint(__uint_as_float(a.x) + __uint_as_float(b.x)), __float_as_uint(__uint_as_float(a.z) + __uint_as_float(b.z)));
      };
      const uint4* c2p = reinterpret_cast<const uint4*>(p.csum + 896 + 128 * tj + 2 * at);
      const uint4* c1p = reinterpret_cast<const uint4*>(p.csum + 128 * tj + 2 * at);
      auto cs_add = [&](const uint4& v) {
        cs[0] += bf_lo(v.x); cs[1] += bf_hi(v.x); cs[2] += bf_lo(v.y); cs[3] += bf_hi(v.y);
        cs[4] += bf_lo(v.z); cs[5] += bf_hi(v.z); cs[6] += bf_lo(v.w); cs[7] += bf_hi(v.w);
      };
      const uint4* wcol = reinterpret_cast<const uint4*>(p.w_in + (size_t)wr * 1792 + 128 * tj + 8 * ti);
      {
        const uint4* src = p.xstat + 128 * ti + 2 * at;
        uint4 v0 = ld_vol4(src), v1 = ld_vol4(src + 1);
        const uint4 ca = ld_vol4(c2p), cb = ld_vol4(c2p + 896);
        const uint4 w6 = __ldg(wcol + (size_t)384 * 224 + 112);
        const uint32_t csa = sb + (ti >> 3) * 8192 + wr * 128 + (((ti & 7) ^ (wr & 7)) * 16);
        #pragma unroll 1
        for (int q = 0; q < 6; q++) {
          mbar_wait(BA(B_WF + q), 0);
          cs_add(lds128(csa + (7 + q) * SLOT));
          if (q < 4) {
            bar_sync(7, 64);
            if (aw == 0) e_arrive_remote(BA(B_WR3 + q), cdst(q + 6));
          }
        }
        cs_add(w6);
        cs_publish(896 + 128 * tj + 8 * ti);
        if (at == 0) { GT(3); }
        #pragma unroll 1
        for (int it = 0; !(ok4(v0) && ok4(v1)) && it < SPIN_LIM; it++) { v0 = ld_vol4(src); v1 = ld_vol4(src + 1); }
        const float ra = __uint_as_float(v0.z), rb = __uint_as_float(v1.z);
        sts128(sb + G_OFF_ROWC + at * 32, v0.x, __float_as_uint(GELU_C0 * ra), __float_as_uint(GELU_C1 * ra * ra * ra), v0.z);
        sts128(sb + G_OFF_ROWC + at * 32 + 16, v1.x, __float_as_uint(GELU_C0 * rb), __float_as_uint(GELU_C1 * rb * rb * rb), v1.z);
        gather_cs(c2p, ca, cb, sb + G_OFF_CS);
        __syncwarp();
        e_arrive(BA(B_PRE));
        if (at == 0) { GT(4); }
        uint4 v[7];
        const uint4* zs = reinterpret_cast<const uint4*>(p.zpart + (size_t)ti * 7 * 128) + at;
        bool ok = false;
        #pragma unroll 1
        for (int it = 0; !ok && it < SPIN_LIM; it++) {
          uint32_t bad = 0;
          #pragma unroll
          for (int c = 0; c < 7; c++) { v[c] = ld_vol4(zs + c * 64); }
          #pragma unroll
          for (int c = 0; c < 7; c++) bad |= (v[c].x ^ E) | (v[c].y ^ E) | (v[c].z ^ E) | (v[c].w ^ E);
          ok = (bad & 0xffu) == 0;
          if (it == 0) { mbar_wait(BA(B_ZPUB), 0); mbar_wait(BA(B_ZPUB + 1), 0); }
        }
        float o[4];
        #pragma unroll
        for (int h = 0; h < 2; h++) {
          float s1 = 0.f, s2 = 0.f;
          #pragma unroll
          for (int c = 0; c < 7; c++) { s1 += __uint_as_float((h ? v[c].z : v[c].x) & ~0xffu); s2 += __uint_as_float((h ? v[c].w : v[c].y) & ~0xffu); }
          const float r = h ? rb : ra;
          const float mean = s1 * (1.f / 896.f);
          const float var = fmaxf(fmaf(s2, 1.f / 896.f, -mean * mean), 0.f);
          const float rs = rsqrtf(var + __fdividef(4e-5f, r * r));
          o[2 * h] = rs; o[2 * h + 1] = -mean * rs;
        }
        sts128(sb + G_OFF_ZST + at * 16, __float_as_uint(o[0]), __float_as_uint(o[1]), __float_as_uint(o[2]), __float_as_uint(o[3]));
      }
      __syncwarp();
      e_arrive(BA(B_ZST));
      if (at == 0) { GT(5); }
      const uint4 c1a = ld_vol4(c1p), c1b = ld_vol4(c1p + 896);
      {
        uint4 w[7];
        #pragma unroll
        for (int q = 0; q < 7; q++) w[q] = __ldg(wcol + (size_t)q * 64 * 224);
        #pragma unroll
        for (int q = 0; q < 7; q++) cs_add(w[q]);
        cs_publish(128 * tj + 8 * ti);
      }
      gather_cs(c1p, c1a, c1b, sb + G_OFF_CS + 512);
      __syncwarp();
      e_arrive(BA(B_PRE1));
      if (2 * tau + aw < 128) {
        const int bt = 2 * tau + aw, cl = min(lane, 27), ch = CONV_CH + 4 * cl;
        uint32_t sh[2][4];
        {
          const uint4* sp = reinterpret_cast<const uint4*>(p.shift_k + (size_t)ch * 4);
          const uint4 a = __ldg(sp), b = __ldg(sp + 1);
          sh[0][0] = prmt(a.x, a.z, 0x5410); sh[0][1] = prmt(a.x, a.z, 0x7632); sh[0][2] = prmt(a.y, a.w, 0x5410); sh[0][3] = prmt(a.y, a.w, 0x7632);
          sh[1][0] = prmt(b.x, b.z, 0x5410); sh[1][1] = prmt(b.x, b.z, 0x7632); sh[1][2] = prmt(b.y, b.w, 0x5410); sh[1][3] = prmt(b.y, b.w, 0x7632);
        }
        const uint2* kp = reinterpret_cast<const uint2*>(p.k + (size_t)16 * bt * 448 + ch);
        const uint2* vp = reinterpret_cast<const uint2*>(p.v + (size_t)16 * bt * 448 + ch);
        auto ld = [&](const uint2* q, int r) { return (r >= 0 || bt > 0) ? __ldg(q + r * 112) : make_uint2(0, 0); };
        unsigned char* tb = p.utab + (size_t)(4 * cl) * CV_TAB + 16 + bt * 32;
        uint2 k3 = ld(kp, -4), k2 = ld(kp, -3), k1 = ld(kp, -2), k0, up;
        uint32_t w[2][4][4];
        #pragma unroll
        for (int r = -1; r < 16; r++) {
          k0 = ld(kp, r);
          const uint2 vv = ld(vp, r);
          uint2 u;
          u.x = hmul2(hfma2(k0.x, sh[0][0], hfma2(k1.x, sh[0][1], hfma2(k2.x, sh[0][2], hmul2(k3.x, sh[0][3])))), vv.x);
          u.y = hmul2(hfma2(k0.y, sh[1][0], hfma2(k1.y, sh[1][1], hfma2(k2.y, sh[1][2], hmul2(k3.y, sh[1][3])))), vv.y);
          k3 = k2; k2 = k1; k1 = k0;
          if (r >= 0) {
            const int cp = r & 1, wi = (r >> 1) & 3;
            w[cp][0][wi] = prmt(u.x, up.x, 0x5410); w[cp][1][wi] = prmt(u.x, up.x, 0x7632);
            w[cp][2][wi] = prmt(u.y, up.y, 0x5410); w[cp][3][wi] = prmt(u.y, up.y, 0x7632);
            if (((r & 7) == 6 || (r & 7) == 7) && lane < 28) {
              #pragma unroll
              for (int c = 0; c < 4; c++)
                *reinterpret_cast<uint4*>(tb + c * CV_TAB + cp * CV_COPY_OFF + (r >> 3) * 16) = make_uint4(w[cp][c][0], w[cp][c][1], w[cp][c][2], w[cp][c][3]);
            }
          }
          up = u;
        }
        __syncwarp();
        if (lane == 0) { __threadfence(); st_relaxed(p.uflag + bt, E); }
        __syncwarp();
      }
      if (aw == 1) {
        bool ok = false;
        #pragma unroll 1
        for (int it = 0; !ok && it < SPIN_LIM; it++) {
          const uint4 f = ld_vol4(reinterpret_cast<const uint4*>(p.uflag) + lane);
          ok = __all_sync(0xffffffffu, f.x == E && f.y == E && f.z == E && f.w == E);
          if (!ok) __nanosleep(100);
        }
        __threadfence();
        fence_async_global();
        if (lane == 0) {
          const float dv = __bfloat162float(p.ssm_D[CONV_CH + tau]);
          bulk_g2s(sb + G_OFF_TAB, p.utab + (size_t)tau * CV_TAB, CV_TAB, BA(B_CVF));
          bulk_g2s(sb + G_OFF_KR + CV_KPAD, p.ssm_k + (size_t)(CONV_CH + tau) * S_, 4096, BA(B_CVF));
          mbar_wait(BA(B_CVF), 0);
          const uint32_t w0 = lds32(sb + G_OFF_KR + CV_KPAD);
          sts32(sb + G_OFF_KR + CV_KPAD, (pack_bf16(bf_lo(w0) + dv, 0.f) & 0xffffu) | (w0 & 0xffff0000u));
          fence_async_smem();
          mbar_arrive(BA(B_CVR));
        }
        __syncwarp();
      }
      mbar_wait(BA(B_HSTG + aw), 0);
      e_store3d_flag(&tm.hst, sb + (10 + aw) * SLOT, 0, 128 * ti + 64 * aw, 2 * tj, p.hflag + ti * 16 + 2 * tj + aw, E);
      e_arrive(BA(B_HFREE + aw));
      if (at == 0) { GT(7); }
      if (aw == 0) {
        mbar_wait(BA(B_YD), 0);
        if (lane == 0) { __threadfence(); st_relaxed(p.yflag + 32 + tau, E); }
        __syncwarp();
      }
      mbar_wait(BA(B_OSTG + aw), 0);
      e_store2d(&tm.out, sb + (10 + aw) * SLOT, 64 * tj, 128 * ti + 64 * aw);
      if (at == 0) { GT(8); }
    }
  } else {
    const int wg = wid >> 2, warp = wid & 3;
    const int g = lane >> 2, t = lane & 3;
    const int row0 = 64 * wg + 16 * warp + g;
    E = ld_relaxed(p.epoch) + 1;
    if (wid >= 3) {
      float s = 0.f;
      #pragma unroll
      for (int r = 0; r < 7; r++) s += (bf_lo(pv[r].x) + bf_hi(pv[r].x)) + (bf_lo(pv[r].y) + bf_hi(pv[r].y)) + (bf_lo(pv[r].z) + bf_hi(pv[r].z)) + (bf_lo(pv[r].w) + bf_hi(pv[r].w));
      s += __shfl_xor_sync(0xffffffffu, s, 1); s += __shfl_xor_sync(0xffffffffu, s, 2); s += __shfl_xor_sync(0xffffffffu, s, 4);
      const float m = s * (1.f / 448.f);
      float q = 0.f, q1 = 0.f;
      #pragma unroll
      for (int r = 0; r < 7; r++) {
        float a;
        a = bf_lo(pv[r].x) - m; q = fmaf(a, a, q); a = bf_hi(pv[r].x) - m; q1 = fmaf(a, a, q1);
        a = bf_lo(pv[r].y) - m; q = fmaf(a, a, q); a = bf_hi(pv[r].y) - m; q1 = fmaf(a, a, q1);
        a = bf_lo(pv[r].z) - m; q = fmaf(a, a, q); a = bf_hi(pv[r].z) - m; q1 = fmaf(a, a, q1);
        a = bf_lo(pv[r].w) - m; q = fmaf(a, a, q); a = bf_hi(pv[r].w) - m; q1 = fmaf(a, a, q1);
      }
      q += q1;
      q += __shfl_xor_sync(0xffffffffu, q, 1); q += __shfl_xor_sync(0xffffffffu, q, 2); q += __shfl_xor_sync(0xffffffffu, q, 4);
      if ((lane & 7) == 0 && xrl < 19 && 19 * tj + xrl < 128) st_vol4(p.xstat + xrow, __float_as_uint(m), E, __float_as_uint(rsqrtf(fmaf(q, 1.f / 448.f, 1e-5f))), E);
    }
    if (tid == 128) { GT(25); }
    reg_inc<G_RC>();
    const uint32_t bsp = __ldg(reinterpret_cast<const unsigned short*>(p.b_sp) + 128 * ti + row0) | ((uint32_t)__ldg(reinterpret_cast<const unsigned short*>(p.b_sp) + 128 * ti + row0 + 8) << 16);
    float acc2[64], acc1[64];
    const uint32_t aoff = sb + wg * 8192;
    const int srow = 16 * warp + ((lane >> 3) & 1) * 8 + (lane & 7);
    const uint32_t sm_row = srow * 128, sm_x = (uint32_t)(lane & 7), sm_c = (uint32_t)(lane >> 4);
    const bool w0 = warp == 0;
    cluster_wait();
    #pragma unroll 1
    for (int b = 0; b < 7; b++) {
      mbar_wait(BA(B_XF + b), 0);
      mbar_wait(BA(B_WF + b), 0);
      if (b == 0 && tid == 0) { GT(10); }
      if (b == 6 && tid == 0) { GT(27); }
      __syncwarp();
      const uint64_t da = dk(aoff + b * SLOT), db = dn(sb + wslot(b) * SLOT);
      wg_fence();
      #pragma unroll
      for (int k = 0; k < 4; k++) WG<128, 0, 1>::ss(acc2, da + 2 * k, db + 128 * k, (b | k) != 0);
      wg_commit();
      if (b > 0) {
        wg_wait<1>();
        if (b < 5 && w0) e_arrive_remote(BA(B_WR3 + b - 1), cdst(b + 5));
      }
    }
    wg_wait<0>();
    if (w0) e_arrive_remote(BA(B_WR + 4), cdst(10));
    if (tid == 0) { GT(11); }
    mbar_wait(BA(B_PRE), 0);
    const uint4 rc0 = lds128(sb + G_OFF_ROWC + row0 * 16), rc1 = lds128(sb + G_OFF_ROWC + (row0 + 8) * 16);
    const float nm0 = -__uint_as_float(rc0.x), A0 = __uint_as_float(rc0.y), B0 = __uint_as_float(rc0.z), rr0 = __uint_as_float(rc0.w);
    const float nm1 = -__uint_as_float(rc1.x), A1 = __uint_as_float(rc1.y), B1 = __uint_as_float(rc1.z), rr1 = __uint_as_float(rc1.w);
    auto gelu2 = [&](float a, float c, float nm, float A, float B) {
      const float tt = fmaf(nm, c, a);
      const float u = tt * fmaf(tt * tt, B, A);
      return fmaf(tt, tanh_fast(u), tt);
    };
    {
      float s10 = 0.f, s20 = 0.f, s11 = 0.f, s21 = 0.f;
      #pragma unroll
      for (int jj = 0; jj < 16; jj++) {
        const uint2 c = lds64(sb + G_OFF_CS + (4 * jj + t) * 8);
        const float c0 = __uint_as_float(c.x), c1 = __uint_as_float(c.y);
        float z;
        z = gelu2(acc2[4 * jj + 0], c0, nm0, A0, B0); acc2[4 * jj + 0] = z; s10 += z; s20 = fmaf(z, z, s20);
        z = gelu2(acc2[4 * jj + 1], c1, nm0, A0, B0); acc2[4 * jj + 1] = z; s10 += z; s20 = fmaf(z, z, s20);
        z = gelu2(acc2[4 * jj + 2], c0, nm1, A1, B1); acc2[4 * jj + 2] = z; s11 += z; s21 = fmaf(z, z, s21);
        z = gelu2(acc2[4 * jj + 3], c1, nm1, A1, B1); acc2[4 * jj + 3] = z; s11 += z; s21 = fmaf(z, z, s21);
      }
      float u0 = (t & 1) ? s10 : s11, k0 = (t & 1) ? s11 : s10;
      float u1 = (t & 1) ? s20 : s21, k1 = (t & 1) ? s21 : s20;
      k0 += __shfl_xor_sync(0xffffffffu, u0, 1); k1 += __shfl_xor_sync(0xffffffffu, u1, 1);
      k0 += __shfl_xor_sync(0xffffffffu, k0, 2); k1 += __shfl_xor_sync(0xffffffffu, k1, 2);
      if (t < 2) st_vol2(p.zpart + (size_t)(ti * 7 + tj) * 128 + row0 + 8 * t, ((__float_as_uint(k0) + 0x80u) & ~0xffu) | (E & 0xffu), ((__float_as_uint(k1) + 0x80u) & ~0xffu) | (E & 0xffu));
      __syncwarp();
      e_arrive(BA(B_ZPUB + wg));
    }
    if (tid == 0) { GT(12); }
    bool zdone = false;
    #pragma unroll 1
    for (int b = 0; b < 7; b++) {
      mbar_wait(BA(B_WF + 7 + b), 0);
      __syncwarp();
      const uint64_t da = dk(aoff + b * SLOT), db = dn(sb + wslot(7 + b) * SLOT);
      wg_fence();
      #pragma unroll
      for (int k = 0; k < 4; k++) WG<128, 0, 1>::ss(acc1, da + 2 * k, db + 128 * k, (b | k) != 0);
      wg_commit();
      if (b > 0) {
        wg_wait<1>();
        const int d = b - 1;
        if (w0) {
          if (d < 3) e_arrive_remote(BA(B_WR + 5 + d), cdst(11 + d));
          const int k = d == 1 ? 0 : d >= 3 ? d - 2 : -1;
          if (k >= 0) { e_arrive_remote(BA(B_RA + k), rdst(k)); e_arrive_remote(BA(B_RB + k), cdst(k)); }
        }
      }
      if (b >= 3 && !zdone) {
        if (b == 6) mbar_wait(BA(B_ZST), 0);
        if (__all_sync(0xffffffffu, mbar_test(BA(B_ZST), 0))) {
          zdone = true;
          TR(zb);
          const uint2 z0 = lds64(sb + G_OFF_ZST + row0 * 8), z1 = lds64(sb + G_OFF_ZST + (row0 + 8) * 8);
          const float a0 = __uint_as_float(z0.x), c0 = __uint_as_float(z0.y), a1 = __uint_as_float(z1.x), c1 = __uint_as_float(z1.y);
          const uint32_t st = sb + (11 + wg) * SLOT + sm_row;
          #pragma unroll
          for (int jp = 0; jp < 8; jp++) {
            const float* d = acc2 + 8 * jp;
            stsm4(st + (jp >> 2) * 8192 + ((((2 * jp) & 7) + sm_c) ^ sm_x) * 16,
                  pack_bf16(fmaf(d[0], a0, c0), fmaf(d[1], a0, c0)), pack_bf16(fmaf(d[2], a1, c1), fmaf(d[3], a1, c1)),
                  pack_bf16(fmaf(d[4], a0, c0), fmaf(d[5], a0, c0)), pack_bf16(fmaf(d[6], a1, c1), fmaf(d[7], a1, c1)));
          }
          fence_async_smem();
          __syncwarp();
          e_arrive(BA(B_ZSTG + wg));
        }
      }
    }
    wg_wait<0>();
    if (w0) {
      mbar_wait(BA(B_ZFREE), 0);
      #pragma unroll
      for (int k = 4; k < 6; k++) { e_arrive_remote(BA(B_RA + k), rdst(k)); e_arrive_remote(BA(B_RB + k), cdst(k)); }
    }
    if (tid == 0) { GT(14); }
    mbar_wait(BA(B_PRE1), 0);
    #pragma unroll
    for (int jj = 0; jj < 16; jj++) {
      const uint2 c = lds64(sb + G_OFF_CS + 512 + (4 * jj + t) * 8);
      const float c0 = __uint_as_float(c.x), c1 = __uint_as_float(c.y);
      acc1[4 * jj + 0] = gelu2(acc1[4 * jj + 0], c0, nm0, A0, B0);
      acc1[4 * jj + 1] = gelu2(acc1[4 * jj + 1], c1, nm0, A0, B0);
      acc1[4 * jj + 2] = gelu2(acc1[4 * jj + 2], c0, nm1, A1, B1);
      acc1[4 * jj + 3] = gelu2(acc1[4 * jj + 3], c1, nm1, A1, B1);
      acc2[4 * jj + 0] = bf_lo(bsp); acc2[4 * jj + 1] = bf_lo(bsp); acc2[4 * jj + 2] = bf_hi(bsp); acc2[4 * jj + 3] = bf_hi(bsp);
    }
    pin<64>(acc2);
    if (tid == 0) { GT(15); }
    {
      int s = 0, sp = 5; uint32_t ph = 0;
      #pragma unroll 1
      for (int k = 0; k < 32; k++) {
        mbar_wait(BA(B_F2 + s), ph);
        if (k == 0 && tid == 0) { GT(16); }
        if (k == 8 && tid == 0) { GT(28); }
        if (k == 20 && tid == 0) { GT(29); }
        __syncwarp();
        const uint64_t da = dk(aoff + aslot(s) * SLOT), db = dn(sb + bslot(s) * SLOT);
        wg_fence();
        #pragma unroll
        for (int kk = 0; kk < 4; kk++) WG<128, 0, 1>::ss(acc2, da + 2 * kk, db + 128 * kk, 1);
        wg_commit();
        if (wid == 1 && k < 26) e_expect(BA(B_F2 + s), 2 * SLOT);
        if (k > 0) {
          wg_wait<1>();
          const int d = k - 1;
          if (w0) {
            if (d < 26) { e_arrive_remote(BA(B_RA + sp), rdst(sp)); e_arrive_remote(BA(B_RB + sp), cdst(sp)); }
            else if (d < 29) e_arrive_remote(BA(B_OR + d - 26), cdst(d - 26));
            else if (d == 29) e_arrive(BA(B_S5));
            else { e_arrive_remote(BA(B_HR + 0), r0); e_arrive_remote(BA(B_HR + 1), rdst(1)); }
          }
        }
        sp = s;
        if (++s == 6) { s = 0; ph ^= 1; }
      }
      wg_wait<0>();
      if (w0) { e_arrive_remote(BA(B_HR + 2), rdst(2)); e_arrive_remote(BA(B_HR + 3), rdst(3)); }
    }
    if (tid == 0) { GT(17); }
    {
      mbar_wait(BA(B_S5), 0);
      const uint32_t st = sb + (10 + wg) * SLOT + sm_row;
      #pragma unroll
      for (int jp = 0; jp < 8; jp++) {
        const float* d = acc2 + 8 * jp; const float* z = acc1 + 8 * jp;
        stsm4(st + (jp >> 2) * 8192 + ((((2 * jp) & 7) + sm_c) ^ sm_x) * 16,
              pack_bf16(d[0] * z[0], d[1] * z[1]), pack_bf16(d[2] * z[2], d[3] * z[3]),
              pack_bf16(d[4] * z[4], d[5] * z[5]), pack_bf16(d[6] * z[6], d[7] * z[7]));
      }
      TR(ha);
      fence_async_smem();
      TR(hb);
      __syncwarp();
      e_arrive(BA(B_HSTG + wg));
    }
    if (tid == 0) { GT(18); }
    if (wg == 0) {
      float d[128];
      uint32_t a[64];
      const int dl = (g >> 1) - t;
      const uint32_t pa = sb + G_OFF_TAB + (g & 1) * CV_COPY_OFF + 16 + 4 * dl + 32 * warp;
      mbar_wait(BA(B_CVR), 0);
      #pragma unroll
      for (int i = 0; i < 16; i++) {
        a[4 * i + 0] = lds32(pa + 256 * i + 16); a[4 * i + 1] = lds32(pa + 256 * i + 144);
        a[4 * i + 2] = lds32(pa + 256 * i); a[4 * i + 3] = lds32(pa + 256 * i + 128);
      }
      const uint32_t db = (((sb + G_OFF_KR + CV_KPAD - 16) & 0x3FFFF) >> 4) | (1u << 16);
      __syncwarp();
      wg_fence();
      ConvMma<0, 0, 16>::run(d, a, db);
      wg_commit();
      mbar_wait(BA(B_HFREE), 0);
      const uint32_t rb = sb + 10 * SLOT;
      if (lane < 2 * warp) sts128(rb + warp * 4096 + lane * 16, 0, 0, 0, 0);
      wg_wait<0>();
      if (tid == 0) { GT(30); }
      const uint32_t rw = rb + warp * 4096 + (2 * warp + lane) * 16;
      #pragma unroll
      for (int b = 0; b < 8; b++) {
        uint32_t o[4];
        #pragma unroll
        for (int m = 0; m < 4; m++) {
          const int jj = 4 * b + m;
          o[m] = jj == 0 ? pack_bf16(d[0], d[1]) : pack_bf16(d[4 * jj] + d[4 * jj - 2], d[4 * jj + 1] + d[4 * jj - 1]);
        }
        stsm4t((b == 7 && 2 * warp + lane >= 32) ? sb + G_OFF_TAB + lane * 16 : rw + b * 512, o[0], o[1], o[2], o[3]);
      }
      bar_sync(6, 128);
      const uint32_t rr = rb + (warp * 64 + lane) * 16;
      uint4 y0 = lds128(rr), y1 = lds128(rr + 512);
      #pragma unroll
      for (int w = 1; w < 4; w++) {
        const uint4 x0 = lds128(rr + w * 4096), x1 = lds128(rr + w * 4096 + 512);
        y0.x = hadd2(y0.x, x0.x); y0.y = hadd2(y0.y, x0.y); y0.z = hadd2(y0.z, x0.z); y0.w = hadd2(y0.w, x0.w);
        y1.x = hadd2(y1.x, x1.x); y1.y = hadd2(y1.y, x1.y); y1.z = hadd2(y1.z, x1.z); y1.w = hadd2(y1.w, x1.w);
      }
      uint4* yo = reinterpret_cast<uint4*>(p.yT + (size_t)(CONV_CH + tau) * S_) + warp * 64 + lane;
      yo[0] = y0; yo[32] = y1;
      __syncwarp();
      e_arrive(BA(B_YD));
      if (tid == 0) { GT(26); }
    }
    float acc3[32];
    {
      #pragma unroll 1
      for (int k = 0; k < 14; k++) {
        if (k == 0 || (k & 3) == 2) mbar_wait(BA(B_OF + ((k + 2) >> 2)), 0);
        mbar_wait(BA(B_HF + (k & 3)), (k >> 2) & 1);
        if (k == 0 && tid == 0) { GT(19); }
        __syncwarp();
        const uint64_t da = dk(aoff + (k & 3) * SLOT), db = dn(sb + oslot(k >> 1) * SLOT + (k & 1) * 8192);
        wg_fence();
        #pragma unroll
        for (int kk = 0; kk < 4; kk++) WG<64, 0, 1>::ss(acc3, da + 2 * kk, db + 128 * kk, (k | kk) != 0);
        wg_commit();
        if (wid == 1 && k < 10) e_expect(BA(B_HF + (k & 3)), SLOT);
        if (k > 0) {
          wg_wait<1>();
          const int d = k - 1;
          if (w0) {
            if (d < 10) e_arrive_remote(BA(B_HR + (d & 3)), rdst(d & 3));
            if (d == 1) e_arrive(BA(B_XR));
            if (d == 3) e_arrive(BA(B_YR));
          }
        }
      }
      wg_wait<0>();
    }
    if (tid == 0) { GT(20); }
    {
      const float r0s = rr0, r1s = rr1;
      const float q0 = 0.25f * r0s, q1 = 0.25f * r1s, e0 = nm0 * r0s, e1 = nm1 * r1s;
      mbar_wait(BA(B_X2F), 0);
      mbar_wait(BA(B_HFREE + wg), 0);
      mbar_wait(BA(B_YF), 0);
      if (tid == 0) { GT(21); }
      const uint32_t xa = sb + oslot(0) * SLOT + wg * 8192 + sm_row;
      const uint32_t ya = sb + oslot(1) * SLOT + wg * 8192 + ((lane >> 4) * 8 + (lane & 7)) * 128 + (((2 * warp + ((lane >> 3) & 1)) ^ (lane & 7)) * 16);
      const uint32_t st = sb + (10 + wg) * SLOT + sm_row;
      #pragma unroll
      for (int jp = 0; jp < 4; jp++) {
        uint32_t xv[4], yv[4], o[4];
        const uint32_t co = ((2 * jp + sm_c) ^ sm_x) * 16;
        ldsm4(xa + co, xv[0], xv[1], xv[2], xv[3]);
        ldsm4t(ya + jp * 2048, yv[0], yv[1], yv[2], yv[3]);
        #pragma unroll
        for (int m = 0; m < 4; m++) {
          const float qs = (m & 1) ? q1 : q0, rs = (m & 1) ? r1s : r0s, es = (m & 1) ? e1 : e0;
          const float xl = bf_lo(xv[m]), xh = bf_hi(xv[m]);
          const float ql = acc3[8 * jp + 2 * m] * qs, qh = acc3[8 * jp + 2 * m + 1] * qs;
          const float gl = fmaf(ql, tanh_fast(ql), ql), gh = fmaf(qh, tanh_fast(qh), qh);
          const float sl = fmaf(xl, rs, es) * bf_lo(yv[m]), sh = fmaf(xh, rs, es) * bf_hi(yv[m]);
          o[m] = pack_bf16(fmaf(sl, gl, xl), fmaf(sh, gh, xh));
        }
        stsm4(st + co, o[0], o[1], o[2], o[3]);
      }
      TR(oa);
      fence_async_smem();
      TR(ob);
      __syncwarp();
      e_arrive(BA(B_OSTG + wg));
    }
    if (tid == 0) { GT(22); }
  }
}

__device__ __align__(1024) __nv_bfloat16 g_z2[2048 * 896];
__device__ __align__(1024) __nv_bfloat16 g_h[2048 * 896];
__device__ __align__(1024) __nv_bfloat16 g_yT[448 * 2048];
__device__ __align__(128) uint4 g_xstat[2048];
__device__ __align__(128) uint2 g_csum[2 * 1792];
__device__ __align__(128) uint2 g_zpart[16 * 7 * 128];
__device__ __align__(128) unsigned char g_utab[112 * CV_TAB];
__device__ __align__(128) uint32_t g_flags[1280];
__device__ long long g_dbg[132 * 128];

typedef CUresult (*EncFn)(CUtensorMap*, CUtensorMapDataType, cuuint32_t, void*, const cuuint64_t*, const cuuint64_t*, const cuuint32_t*, const cuuint32_t*,
                          CUtensorMapInterleave, CUtensorMapSwizzle, CUtensorMapL2promotion, CUtensorMapFloatOOBfill);

static void enc_map(EncFn enc, CUtensorMap* m, const void* ptr, int rank, const cuuint64_t* gd, const cuuint64_t* gs, const cuuint32_t* bd, bool swz) {
  cuuint32_t es[3] = {1, 1, 1};
  enc(m, CU_TENSOR_MAP_DATA_TYPE_BFLOAT16, rank, const_cast<void*>(ptr), gd, gs, bd, es, CU_TENSOR_MAP_INTERLEAVE_NONE,
      swz ? CU_TENSOR_MAP_SWIZZLE_128B : CU_TENSOR_MAP_SWIZZLE_NONE, swz ? CU_TENSOR_MAP_L2_PROMOTION_L2_128B : CU_TENSOR_MAP_L2_PROMOTION_NONE, CU_TENSOR_MAP_FLOAT_OOB_FILL_NONE);
}
static void map2d(EncFn e, CUtensorMap* m, const void* p, int rows, int cols, int brows) {
  cuuint64_t gd[2] = {(cuuint64_t)cols, (cuuint64_t)rows}, gs[1] = {(cuuint64_t)cols * 2}; cuuint32_t bd[2] = {64, (cuuint32_t)brows};
  enc_map(e, m, p, 2, gd, gs, bd, true);
}
static void map3d(EncFn e, CUtensorMap* m, const void* p, int rows, int cols) {
  cuuint64_t gd[3] = {64, (cuuint64_t)rows, (cuuint64_t)(cols / 64)}, gs[2] = {(cuuint64_t)cols * 2, 128}; cuuint32_t bd[3] = {64, 64, 2};
  enc_map(e, m, p, 3, gd, gs, bd, true);
}
static void mapraw(EncFn e, CUtensorMap* m, const void* p) {
  cuuint64_t gd[3] = {448, 128, 16}, gs[2] = {16 * 896, 896}; cuuint32_t bd[3] = {8, CV_RAW_BLK, 16};
  enc_map(e, m, p, 3, gd, gs, bd, false);
}

extern "C" void kernel_launch(void* const* d_in, const int* in_sizes, int n_in, void* d_out, int out_size) {
  static GemmMaps gm; static CUtensorMap tk, tv; static GemmParams gp; static ConvParams cp;
  static const void* key[12] = {};
  bool same = true;
  for (int i = 0; i < 11; i++) same = same && key[i] == d_in[i];
  same = same && key[11] == d_out;
  if (!same) {
    for (int i = 0; i < 11; i++) key[i] = d_in[i];
    key[11] = d_out;
    void* fn = nullptr; cudaDriverEntryPointQueryResult qr;
    cudaGetDriverEntryPoint("cuTensorMapEncodeTiled", &fn, cudaEnableDefault, &qr);
    EncFn enc = (EncFn)fn;
    void *z2, *h, *yT, *xs, *cs, *zp, *fl, *dbg, *ut;
    cudaGetSymbolAddress(&ut, g_utab);
    cudaGetSymbolAddress(&z2, g_z2); cudaGetSymbolAddress(&h, g_h); cudaGetSymbolAddress(&yT, g_yT); cudaGetSymbolAddress(&xs, g_xstat);
    cudaGetSymbolAddress(&cs, g_csum); cudaGetSymbolAddress(&zp, g_zpart); cudaGetSymbolAddress(&fl, g_flags); cudaGetSymbolAddress(&dbg, g_dbg);
    map2d(enc, &gm.x, d_in[0], 2048, 448, 128);
    map3d(enc, &gm.win, d_in[7], 448, 1792);
    map2d(enc, &gm.wsp, d_in[8], 2048, 2048, 128);
    map3d(enc, &gm.z2, z2, 2048, 896);
    map2d(enc, &gm.hld, h, 2048, 896, 128);
    map3d(enc, &gm.hst, h, 2048, 896);
    map2d(enc, &gm.wout, d_in[10], 896, 448, 128);
    map3d(enc, &gm.y, yT, 448, 2048);
    map2d(enc, &gm.out, d_out, 2048, 448, 64);
    mapraw(enc, &tk, d_in[1]); mapraw(enc, &tv, d_in[2]);
    uint32_t* f = (uint32_t*)fl;
    gp = GemmParams{(const __nv_bfloat16*)d_in[0], (const __nv_bfloat16*)d_in[7], (const __nv_bfloat16*)d_in[9],
                    (const __nv_bfloat16*)d_in[1], (const __nv_bfloat16*)d_in[2], (const __nv_bfloat16*)d_in[3], (const __nv_bfloat16*)d_in[4], (const __nv_bfloat16*)d_in[5],
                    (unsigned char*)ut, (__nv_bfloat16*)yT, f + 1024, (uint4*)xs, (uint2*)cs, (uint2*)zp,
                    f, f + 256, f + 512, f + 800, f + 672, (long long*)dbg};
    cp = ConvParams{(const __nv_bfloat16*)d_in[1], (const __nv_bfloat16*)d_in[2], (const __nv_bfloat16*)d_in[3], (const __nv_bfloat16*)d_in[4], (const __nv_bfloat16*)d_in[5], (__nv_bfloat16*)yT, f + 512, f + 800, f + 672, f + 832,
                    (long long*)dbg + 112 * 32};
    cudaFuncSetAttribute(gemm_kernel, cudaFuncAttributeMaxDynamicSharedMemorySize, G_SMEM);
    cudaFuncSetAttribute(gemm_kernel, cudaFuncAttributeNonPortableClusterSizeAllowed, 1);
    cudaFuncSetAttribute(conv_kernel, cudaFuncAttributeMaxDynamicSharedMemorySize, CV_SMEM);
  }
  cudaStream_t st = cudaStreamPerThread;
  {
    cudaLaunchConfig_t cfg = {}; cfg.gridDim = dim3(G_CTAS); cfg.blockDim = dim3(384); cfg.dynamicSmemBytes = G_SMEM; cfg.stream = st;
    cudaLaunchAttribute at[1]; at[0].id = cudaLaunchAttributeClusterDimension; at[0].val.clusterDim.x = 16; at[0].val.clusterDim.y = 1; at[0].val.clusterDim.z = 1;
    cfg.attrs = at; cfg.numAttrs = 1;
    cudaLaunchKernelEx(&cfg, gemm_kernel, gm, gp);
  }
  {
    cudaLaunchConfig_t cfg = {}; cfg.gridDim = dim3(CONV_CTAS); cfg.blockDim = dim3(384); cfg.dynamicSmemBytes = CV_SMEM; cfg.stream = st;
    cudaLaunchAttribute at[1]; at[0].id = cudaLaunchAttributeProgrammaticStreamSerialization; at[0].val.programmaticStreamSerializationAllowed = 1;
    cfg.attrs = at; cfg.numAttrs = 1;
    cudaLaunchKernelEx(&cfg, conv_kernel, tk, tv, cp);
  }
}
```
